```python
import torch

def _softmax(x, axis=-1):
    return torch.softmax(x, dim=axis)
def _gelu(x):
    return torch.nn.functional.gelu(x, approximate="tanh")
def _silu(x):
    return torch.nn.functional.silu(x)
def _sigmoid(x):
    return torch.sigmoid(x)
def _layernorm(x, axis=-1, eps=1e-5):
    m = x.mean(dim=axis, keepdim=True)
    v = x.var(dim=axis, keepdim=True, unbiased=False)
    return (x - m) / torch.sqrt(v + eps)
def _scatter_add(tgt, idx, src, axis=0):
    return tgt.clone().index_add_(axis, idx, src)
def _segment_sum(src, seg, n):
    out = torch.zeros((n,) + src.shape[1:], dtype=src.dtype)
    return out.index_add_(0, seg, src)
def _pad(x, pw):
    flat = tuple(v for pair in reversed(pw) for v in pair)
    return torch.nn.functional.pad(x, flat)

kernel_name = 'interleave_layers__ssm_conv_s4d__glu_gated_glu__prompt'

def setup_inputs():

    _w = (lambda a: (lambda t: t.to(torch.bfloat16) if t.is_floating_point() else t)(torch.as_tensor(a)))
    def _A_setup():
        Bsz, L, D, N = 1, 2048, 512, 128
        return {
            "u": _w((lambda *s: torch.randn(*s, dtype=torch.bfloat16) * 0.05)(Bsz, L, D)),
            "log_A_real": _w((lambda *s: torch.randn(*s, dtype=torch.bfloat16) * 3.2)(D, N) * 0.5),
            "A_imag": _w((lambda *s: torch.randn(*s, dtype=torch.bfloat16) * 0.1)(D, N) * 3.14),
            "C_real": _w((lambda *s: torch.randn(*s, dtype=torch.bfloat16) * 0.1)(D, N) / N ** 0.5),
            "C_imag": _w((lambda *s: torch.randn(*s, dtype=torch.bfloat16) * 0.1)(D, N) / N ** 0.5),
            "log_dt": _w((lambda *s: torch.randn(*s, dtype=torch.bfloat16) * 0.1)(D) * 0.5 - 4.0),
            "D_skip": _w((lambda *s: torch.randn(*s, dtype=torch.bfloat16) * 0.1)(D)),
        }
    _A_in = _A_setup()

    def _B_setup():
        B, S, D, F = 1, 2048, 512, 1376
        return {
            "x": _w((lambda *s: torch.randn(*s, dtype=torch.bfloat16) * 0.05)(B, S, D)),
            "w_gate": _w((lambda *s: torch.randn(*s, dtype=torch.bfloat16) * 0.05)(D, F)),
            "w_up": _w((lambda *s: torch.randn(*s, dtype=torch.bfloat16) * 0.05)(D, F)),
            "w_down": _w((lambda *s: torch.randn(*s, dtype=torch.bfloat16) * 0.05)(F, D)),
        }
    _B_in = _B_setup()

    return {
        "A_u": _A_in["u"],
        "A_log_A_real": _A_in["log_A_real"],
        "A_A_imag": _A_in["A_imag"],
        "A_C_real": _A_in["C_real"],
        "A_C_imag": _A_in["C_imag"],
        "A_log_dt": _A_in["log_dt"],
        "A_D_skip": _A_in["D_skip"],
        "B_x": _B_in["x"],
        "B_w_gate": _B_in["w_gate"],
        "B_w_up": _B_in["w_up"],
        "B_w_down": _B_in["w_down"],
    }

def reference(A_u, A_log_A_real, A_A_imag, A_C_real, A_C_imag, A_log_dt, A_D_skip, B_x, B_w_gate, B_w_up, B_w_down):
    def _A_ref(u, log_A_real, A_imag, C_real, C_imag, log_dt, D_skip):
        L = u.shape[1]
        dt = torch.exp(log_dt)
        A = -torch.exp(log_A_real) + 1j * A_imag
        C = (C_real + 1j * C_imag) * dt[:, None]
        pos = (lambda x, dt: x.to(dt))(torch.arange(L), log_dt.dtype)
        P = torch.exp((A * dt[:, None])[:, :, None] * pos[None, None, :])
        K = 2.0 * torch.einsum("dn,dnl->dl", C, P).real
        L2 = 2 * L
        u_t = (lambda x, *d: x.permute(*d))(u, 0, 2, 1)
        Kf = (lambda x, *a, **k: torch.fft.rfft(x.float(), *a, **k))(K, L2)
        Uf = (lambda x, *a, **k: torch.fft.rfft(x.float(), *a, **k))(u_t, L2)
        y = (lambda x, *a, **k: torch.fft.irfft(x, *a, **k).to(torch.bfloat16))(Uf * Kf[None, :, :], L2)[:, :, :L]
        y = (lambda x, *d: x.permute(*d))(y, 0, 2, 1)
        return y + u * D_skip[None, None, :]

    def _B_ref(x, w_gate, w_up, w_down):
        g = torch.einsum("bsd,df->bsf", x, w_gate)
        u = torch.einsum("bsd,df->bsf", x, w_up)
        h = _sigmoid(g) * u
        return torch.einsum("bsf,fd->bsd", h, w_down)

    x = A_u
    x = x + _A_ref(_layernorm(x, axis=-1), A_log_A_real, A_A_imag, A_C_real, A_C_imag, A_log_dt, A_D_skip)
    x = x + _B_ref(_layernorm(x, axis=-1), B_w_gate, B_w_up, B_w_down)
    x = x + _A_ref(_layernorm(x, axis=-1), A_log_A_real, A_A_imag, A_C_real, A_C_imag, A_log_dt, A_D_skip)
    x = x + _B_ref(_layernorm(x, axis=-1), B_w_gate, B_w_up, B_w_down)
    return x
```

```cpp
#include <cuda_runtime.h>
#include <cuda.h>
#include <cuda_bf16.h>
#include <cuda_fp16.h>
#include <stdint.h>
#include <string.h>

namespace {

constexpr int SEQ = 2048, DM = 512, NMODE = 128, FF = 1376;
constexpr int NCTA = 128, NTHREADS = 384;

constexpr int SM_X = 0;
constexpr int SM_W = 131072;
constexpr int SM_MISC = 229376;
constexpr int SM_TOTAL = 232448;
constexpr int SM_BAR = SM_MISC;
constexpr int SM_STAT = SM_MISC + 400;
constexpr int SM_CS = SM_MISC + 1424;
constexpr int SM_SCR = SM_MISC + 2832;
constexpr int SM_TN = 0, TN_CH = 2560;
constexpr int SM_TF = 10240, TF_CH = 1664;
constexpr int SM_SC = 16896;
constexpr int TAB_BYTES = 16912;
constexpr int SM_KV = 16912;
constexpr int SM_US = 36864, US_CH = 4352;
constexpr int SM_G = 54272, G_CH = 10368;
constexpr int SM_YS = 96256;
constexpr int SM_CX = 112640;
constexpr int SM_FA = 40960;
constexpr int SM_FB = SM_FA + 4 * 48 * 528;
__device__ __forceinline__ uint32_t g2_wblk(int kb) {
  const int q = kb < 6 ? kb : kb - 6;
  return q < 3 ? SM_X + q * 16384 : SM_W + (q - 3) * 32768;
}
__device__ __forceinline__ uint32_t g2_hblk(int kb) {
  const int q = kb < 6 ? kb : kb - 6;
  return q < 3 ? SM_X + (q + 3) * 16384 : SM_W + (q - 3) * 32768 + 16384;
}
constexpr int SM_RES = SM_W + 65536;
constexpr int SM_RED = SM_W + 65536 + 16384;
constexpr int SM_XCH = SM_X + 98304;

constexpr int B_WFULL = 0, B_WEMPTY = 4, B_G = 8, B_HC = 15, B_G2FULL = 16, B_G2EMPTY = 27;
constexpr int B_STAT = 38, B_HA = 39, B_HB = 40, B_XFREE = 41, B_XCH = 42, B_RES = 43, B_PT = 44, B_KG = 45, B_TP = 46, B_CM = 47, B_PX = 48, B_PW = 49, B_NUM = 50;

constexpr int W1_SLICE = 8 * 24576 + 8 * 20480;
__device__ __align__(1024) __nv_bfloat16 g_x[4][SEQ * DM];
__device__ __align__(1024) unsigned char g_w1p[8 * W1_SLICE];
__device__ __align__(1024) unsigned char g_w2p[2 * 4 * 11 * 16384];
__device__ __align__(1024) unsigned char g_h[16 * 2 * 11 * 16384];
__device__ __align__(1024) unsigned char g_tab[NCTA * 17408];
__device__ __align__(128) float g_csp[8][8 * 352];
__device__ __align__(128) float2 g_statp[5][SEQ];
__device__ unsigned g_ctr[64 * 32];
__device__ unsigned g_epoch;
constexpr int C_T1 = 0, C_PACK = 1, C_T2 = 2, C_T3 = 3, C_T4 = 4;
__device__ unsigned g_ctr2[2 * 6 * 32 * 32];

#define TL(i) do {} while (0)
#define TLP(i) do {} while (0)
struct Params {
  CUtensorMap tmX, tmG, tmU, tmD;
  const __nv_bfloat16 *x0, *logA, *Aim, *Cre, *Cim, *logdt, *Dskip, *Wg, *Wu, *Wd;
  __nv_bfloat16* out;
  int mask;
};

__device__ __forceinline__ uint32_t smem_u32(const void* p) { return (uint32_t)__cvta_generic_to_shared(p); }
__device__ __forceinline__ void mbar_init(uint32_t a, uint32_t c) { asm volatile("mbarrier.init.shared::cta.b64 [%0], %1;" ::"r"(a), "r"(c)); }
__device__ __forceinline__ void mbar_expect(uint32_t a, uint32_t b) { asm volatile("mbarrier.arrive.expect_tx.shared::cta.b64 _, [%0], %1;" ::"r"(a), "r"(b) : "memory"); }
__device__ __forceinline__ void mbar_arrive(uint32_t a) { asm volatile("mbarrier.arrive.shared::cta.b64 _, [%0];" ::"r"(a) : "memory"); }
__device__ __forceinline__ void mbar_arrive_remote(uint32_t a) { asm volatile("mbarrier.arrive.relaxed.cluster.shared::cluster.b64 _, [%0];" ::"r"(a) : "memory"); }
__device__ __forceinline__ void mbar_wait(uint32_t a, uint32_t ph) {
  asm volatile("{\n.reg .pred p;\n.reg .u32 c;\nmov.u32 c, 0;\nW_LOOP:\n"
               "mbarrier.try_wait.parity.shared::cta.b64 p, [%0], %1;\n@p bra.uni W_DONE;\n"
               "add.u32 c, c, 1;\nsetp.lt.u32 p, c, 0x1000000;\n@p bra.uni W_LOOP;\ntrap;\nW_DONE:\n}" ::"r"(a), "r"(ph) : "memory");
}
__device__ __forceinline__ uint32_t mapa(uint32_t a, uint32_t rank) { uint32_t r; asm("mapa.shared::cluster.u32 %0, %1, %2;" : "=r"(r) : "r"(a), "r"(rank)); return r; }
__device__ __forceinline__ void bulk_g2s(uint32_t dst, const void* src, uint32_t bytes, uint32_t bar) {
  asm volatile("cp.async.bulk.shared::cluster.global.mbarrier::complete_tx::bytes [%0], [%1], %2, [%3];" ::"r"(dst), "l"(src), "r"(bytes), "r"(bar) : "memory");
}
__device__ __forceinline__ void bulk_s2g(void* dst, uint32_t src, uint32_t bytes) {
  asm volatile("cp.async.bulk.global.shared::cta.bulk_group [%0], [%1], %2;" ::"l"(dst), "r"(src), "r"(bytes) : "memory");
}
__device__ __forceinline__ void bulk_commit() { asm volatile("cp.async.bulk.commit_group;" ::: "memory"); }
__device__ __forceinline__ void bulk_wait_all() { asm volatile("cp.async.bulk.wait_group 0;" ::: "memory"); }
__device__ __forceinline__ void fence_async_smem() { asm volatile("fence.proxy.async.shared::cta;" ::: "memory"); }
template <int ID, int N> __device__ __forceinline__ void named_sync_c() { asm volatile("bar.sync %0, %1;" ::"n"(ID), "n"(N) : "memory"); }
__device__ __forceinline__ void wg_sync(int wg) { if (wg == 0) named_sync_c<2, 128>(); else named_sync_c<3, 128>(); }
__device__ __forceinline__ void readback_lines(const unsigned char* p, int off) {
  unsigned v0, v1;
  int it = 0;
  do {
    asm volatile("ld.relaxed.gpu.global.u32 %0, [%1];" : "=r"(v0) : "l"(p + 124) : "memory");
    asm volatile("ld.relaxed.gpu.global.u32 %0, [%1];" : "=r"(v1) : "l"(p + off + 124) : "memory");
  } while (!__all_sync(~0u, v0 != 0xFFFFFFFFu && v1 != 0xFFFFFFFFu) && ++it < 2);
}
__device__ __forceinline__ void red_release(unsigned* p) { asm volatile("red.release.gpu.global.add.u32 [%0], 1;" ::"l"(p) : "memory"); }
__device__ __forceinline__ void red_relaxed(unsigned* p) { asm volatile("red.relaxed.gpu.global.add.u32 [%0], 1;" ::"l"(p) : "memory"); }
__device__ __forceinline__ void poll_ge(const unsigned* p, unsigned target) {
  asm volatile("{\n.reg .pred p;\n.reg .u32 c, v;\n.reg .s32 d;\nmov.u32 c, 0;\nP_LOOP:\n"
               "ld.relaxed.gpu.global.u32 v, [%0];\nsub.s32 d, v, %1;\nsetp.ge.s32 p, d, 0;\n@p bra P_DONE;\n"
               "add.u32 c, c, 1;\nsetp.lt.u32 p, c, 0x400000;\n@p bra P_LOOP;\ntrap;\nP_DONE:\n}" ::"l"(p), "r"(target) : "memory");
}
__device__ __forceinline__ void wgmma_fence() { asm volatile("wgmma.fence.sync.aligned;" ::: "memory"); }
__device__ __forceinline__ void wgmma_commit() { asm volatile("wgmma.commit_group.sync.aligned;" ::: "memory"); }
template <int N> __device__ __forceinline__ void wgmma_wait() { asm volatile("wgmma.wait_group.sync.aligned %0;" ::"n"(N) : "memory"); }
template <int N> __device__ __forceinline__ void reg_fence(float (&d)[N]) {
#pragma unroll
  for (int i = 0; i < N; i++) asm volatile("" : "+f"(d[i])::"memory");
}
template <int N> __device__ __forceinline__ void reg_def(float (&d)[N]) {
#pragma unroll
  for (int i = 0; i < N; i++) asm volatile("mov.b32 %0, 0;" : "=f"(d[i]));
}
__device__ __forceinline__ void ldsm_x4(uint32_t& r0, uint32_t& r1, uint32_t& r2, uint32_t& r3, uint32_t a) {
  asm volatile("ldmatrix.sync.aligned.m8n8.x4.shared.b16 {%0,%1,%2,%3}, [%4];" : "=r"(r0), "=r"(r1), "=r"(r2), "=r"(r3) : "r"(a) : "memory");
}
__device__ __forceinline__ void stsm_x4(uint32_t a, uint32_t r0, uint32_t r1, uint32_t r2, uint32_t r3) {
  asm volatile("stmatrix.sync.aligned.m8n8.x4.shared.b16 [%0], {%1,%2,%3,%4};" ::"r"(a), "r"(r0), "r"(r1), "r"(r2), "r"(r3) : "memory");
}
__device__ __forceinline__ void stsm_x4_t(uint32_t a, uint32_t r0, uint32_t r1, uint32_t r2, uint32_t r3) {
  asm volatile("stmatrix.sync.aligned.m8n8.x4.trans.shared.b16 [%0], {%1,%2,%3,%4};" ::"r"(a), "r"(r0), "r"(r1), "r"(r2), "r"(r3) : "memory");
}
__device__ __forceinline__ void mma_f16(float (&c)[4], uint32_t a0, uint32_t a1, uint32_t a2, uint32_t a3, uint32_t b0, uint32_t b1) {
  asm volatile("mma.sync.aligned.m16n8k16.row.col.f32.f16.f16.f32 {%0,%1,%2,%3}, {%4,%5,%6,%7}, {%8,%9}, {%0,%1,%2,%3};"
               : "+f"(c[0]), "+f"(c[1]), "+f"(c[2]), "+f"(c[3]) : "r"(a0), "r"(a1), "r"(a2), "r"(a3), "r"(b0), "r"(b1));
}
__device__ __forceinline__ uint4 lds128(uint32_t a) { uint4 v; asm volatile("ld.shared.v4.b32 {%0,%1,%2,%3}, [%4];" : "=r"(v.x), "=r"(v.y), "=r"(v.z), "=r"(v.w) : "r"(a)); return v; }
__device__ __forceinline__ void sts128(uint32_t a, uint4 v) { asm volatile("st.shared.v4.b32 [%0], {%1,%2,%3,%4};" ::"r"(a), "r"(v.x), "r"(v.y), "r"(v.z), "r"(v.w) : "memory"); }
__device__ __forceinline__ void sts32(uint32_t a, uint32_t v) { asm volatile("st.shared.b32 [%0], %1;" ::"r"(a), "r"(v) : "memory"); }
__device__ __forceinline__ float bf_lo(uint32_t v) { return __uint_as_float(v << 16); }
__device__ __forceinline__ float bf_hi(uint32_t v) { return __uint_as_float(v & 0xFFFF0000u); }
__device__ __forceinline__ uint32_t pack_bf(float lo, float hi) { uint32_t r; asm("cvt.rn.bf16x2.f32 %0, %1, %2;" : "=r"(r) : "f"(hi), "f"(lo)); return r; }
__device__ __forceinline__ uint32_t pack_h(float lo, float hi) { uint32_t r; asm("cvt.rn.f16x2.f32 %0, %1, %2;" : "=r"(r) : "f"(hi), "f"(lo)); return r; }
__device__ __forceinline__ float bf_round(float v) { return __bfloat162float(__float2bfloat16_rn(v)); }
__device__ __forceinline__ float ex2(float x) { float r; asm("ex2.approx.ftz.f32 %0, %1;" : "=f"(r) : "f"(x)); return r; }
__device__ __forceinline__ float rcp(float x) { float r; asm("rcp.approx.ftz.f32 %0, %1;" : "=f"(r) : "f"(x)); return r; }
__device__ __forceinline__ float tanh_hw(float x) { float r; asm("tanh.approx.f32 %0, %1;" : "=f"(r) : "f"(x)); return r; }
__device__ __forceinline__ float ldbf(const __nv_bfloat16* p) { return __bfloat162float(*p); }
__device__ __forceinline__ float sqrt_approx(float x) { float r; asm("sqrt.approx.ftz.f32 %0, %1;" : "=f"(r) : "f"(x)); return r; }
__device__ __forceinline__ uint32_t badd2(uint32_t a, uint32_t b) { uint32_t r; asm("add.rn.bf16x2 %0, %1, %2;" : "=r"(r) : "r"(a), "r"(b)); return r; }
__device__ __forceinline__ uint32_t bsub2(uint32_t a, uint32_t b) { uint32_t r; asm("sub.rn.bf16x2 %0, %1, %2;" : "=r"(r) : "r"(a), "r"(b)); return r; }
__device__ __forceinline__ uint32_t bmul2(uint32_t a, uint32_t b) { uint32_t r; asm("mul.rn.bf16x2 %0, %1, %2;" : "=r"(r) : "r"(a), "r"(b)); return r; }
template <int NV, int MASK> __device__ __forceinline__ void xreduce(float* v, int lane) {
  const bool up = lane & MASK;
#pragma unroll
  for (int q = 0; q < NV / 2; q++) {
    const float keep = up ? v[q + NV / 2] : v[q], send = up ? v[q] : v[q + NV / 2];
    v[q] = keep + __shfl_xor_sync(~0u, send, MASK);
  }
}

__device__ __forceinline__ void ln_finish2(float s0, float q0, float s1, float q1, uint32_t& mean2, uint32_t& std2) {
  const float m0 = s0 * (1.0f / DM), m1 = s1 * (1.0f / DM);
  const float v0 = fmaxf(fmaf(-m0, m0, q0 * (1.0f / DM)), 0.0f), v1 = fmaxf(fmaf(-m1, m1, q1 * (1.0f / DM)), 0.0f);
  mean2 = pack_bf(m0, m1);
  const uint32_t v2 = pack_bf(v0, v1);
  const uint32_t e2 = pack_bf(bf_lo(v2) + 1e-5f, bf_hi(v2) + 1e-5f);
  std2 = pack_bf(sqrt_approx(bf_lo(e2)), sqrt_approx(bf_hi(e2)));
}

__device__ __forceinline__ int ximg_chunk(int c, int d) {
  int r = c >> 4, w = (c >> 3) & 1, ch = c & 7, kb = d >> 6, dl = d & 63;
  return ((((r * 8 + kb) * 2 + w) * 64 + dl) << 6) + ((ch ^ (dl & 7)) << 3);
}

__device__ __forceinline__ void wgmma_n192_tt(float (&d)[96], uint32_t alo, uint32_t blo) {
  asm volatile("{\n.reg .b64 da, db;\nmov.b64 da, {%96, 0x40000040};\nmov.b64 db, {%97, 0x800000c0};\n"
    "wgmma.mma_async.sync.aligned.m64n192k16.f32.bf16.bf16 "
    "{%0, %1, %2, %3, %4, %5, %6, %7, %8, %9, %10, %11, %12, %13, %14, %15, "
    "%16, %17, %18, %19, %20, %21, %22, %23, %24, %25, %26, %27, %28, %29, %30, %31, "
    "%32, %33, %34, %35, %36, %37, %38, %39, %40, %41, %42, %43, %44, %45, %46, %47, "
    "%48, %49, %50, %51, %52, %53, %54, %55, %56, %57, %58, %59, %60, %61, %62, %63, "
    "%64, %65, %66, %67, %68, %69, %70, %71, %72, %73, %74, %75, %76, %77, %78, %79, "
    "%80, %81, %82, %83, %84, %85, %86, %87, %88, %89, %90, %91, %92, %93, %94, %95}, "
    "da, db, 1, 1, 1, 1, 1;\n}\n"
    : "+f"(d[0]), "+f"(d[1]), "+f"(d[2]), "+f"(d[3]), "+f"(d[4]), "+f"(d[5]), "+f"(d[6]), "+f"(d[7]),
      "+f"(d[8]), "+f"(d[9]), "+f"(d[10]), "+f"(d[11]), "+f"(d[12]), "+f"(d[13]), "+f"(d[14]), "+f"(d[15]),
      "+f"(d[16]), "+f"(d[17]), "+f"(d[18]), "+f"(d[19]), "+f"(d[20]), "+f"(d[21]), "+f"(d[22]), "+f"(d[23]),
      "+f"(d[24]), "+f"(d[25]), "+f"(d[26]), "+f"(d[27]), "+f"(d[28]), "+f"(d[29]), "+f"(d[30]), "+f"(d[31]),
      "+f"(d[32]), "+f"(d[33]), "+f"(d[34]), "+f"(d[35]), "+f"(d[36]), "+f"(d[37]), "+f"(d[38]), "+f"(d[39]),
      "+f"(d[40]), "+f"(d[41]), "+f"(d[42]), "+f"(d[43]), "+f"(d[44]), "+f"(d[45]), "+f"(d[46]), "+f"(d[47]),
      "+f"(d[48]), "+f"(d[49]), "+f"(d[50]), "+f"(d[51]), "+f"(d[52]), "+f"(d[53]), "+f"(d[54]), "+f"(d[55]),
      "+f"(d[56]), "+f"(d[57]), "+f"(d[58]), "+f"(d[59]), "+f"(d[60]), "+f"(d[61]), "+f"(d[62]), "+f"(d[63]),
      "+f"(d[64]), "+f"(d[65]), "+f"(d[66]), "+f"(d[67]), "+f"(d[68]), "+f"(d[69]), "+f"(d[70]), "+f"(d[71]),
      "+f"(d[72]), "+f"(d[73]), "+f"(d[74]), "+f"(d[75]), "+f"(d[76]), "+f"(d[77]), "+f"(d[78]), "+f"(d[79]),
      "+f"(d[80]), "+f"(d[81]), "+f"(d[82]), "+f"(d[83]), "+f"(d[84]), "+f"(d[85]), "+f"(d[86]), "+f"(d[87]),
      "+f"(d[88]), "+f"(d[89]), "+f"(d[90]), "+f"(d[91]), "+f"(d[92]), "+f"(d[93]), "+f"(d[94]), "+f"(d[95])
    : "r"(alo), "r"(blo));
}
__device__ __forceinline__ void wgmma_n160_tt(float (&d)[80], uint32_t alo, uint32_t blo) {
  asm volatile("{\n.reg .b64 da, db;\nmov.b64 da, {%80, 0x40000040};\nmov.b64 db, {%81, 0x800000a0};\n"
    "wgmma.mma_async.sync.aligned.m64n160k16.f32.bf16.bf16 "
    "{%0, %1, %2, %3, %4, %5, %6, %7, %8, %9, %10, %11, %12, %13, %14, %15, "
    "%16, %17, %18, %19, %20, %21, %22, %23, %24, %25, %26, %27, %28, %29, %30, %31, "
    "%32, %33, %34, %35, %36, %37, %38, %39, %40, %41, %42, %43, %44, %45, %46, %47, "
    "%48, %49, %50, %51, %52, %53, %54, %55, %56, %57, %58, %59, %60, %61, %62, %63, "
    "%64, %65, %66, %67, %68, %69, %70, %71, %72, %73, %74, %75, %76, %77, %78, %79}, "
    "da, db, 1, 1, 1, 1, 1;\n}\n"
    : "+f"(d[0]), "+f"(d[1]), "+f"(d[2]), "+f"(d[3]), "+f"(d[4]), "+f"(d[5]), "+f"(d[6]), "+f"(d[7]),
      "+f"(d[8]), "+f"(d[9]), "+f"(d[10]), "+f"(d[11]), "+f"(d[12]), "+f"(d[13]), "+f"(d[14]), "+f"(d[15]),
      "+f"(d[16]), "+f"(d[17]), "+f"(d[18]), "+f"(d[19]), "+f"(d[20]), "+f"(d[21]), "+f"(d[22]), "+f"(d[23]),
      "+f"(d[24]), "+f"(d[25]), "+f"(d[26]), "+f"(d[27]), "+f"(d[28]), "+f"(d[29]), "+f"(d[30]), "+f"(d[31]),
      "+f"(d[32]), "+f"(d[33]), "+f"(d[34]), "+f"(d[35]), "+f"(d[36]), "+f"(d[37]), "+f"(d[38]), "+f"(d[39]),
      "+f"(d[40]), "+f"(d[41]), "+f"(d[42]), "+f"(d[43]), "+f"(d[44]), "+f"(d[45]), "+f"(d[46]), "+f"(d[47]),
      "+f"(d[48]), "+f"(d[49]), "+f"(d[50]), "+f"(d[51]), "+f"(d[52]), "+f"(d[53]), "+f"(d[54]), "+f"(d[55]),
      "+f"(d[56]), "+f"(d[57]), "+f"(d[58]), "+f"(d[59]), "+f"(d[60]), "+f"(d[61]), "+f"(d[62]), "+f"(d[63]),
      "+f"(d[64]), "+f"(d[65]), "+f"(d[66]), "+f"(d[67]), "+f"(d[68]), "+f"(d[69]), "+f"(d[70]), "+f"(d[71]),
      "+f"(d[72]), "+f"(d[73]), "+f"(d[74]), "+f"(d[75]), "+f"(d[76]), "+f"(d[77]), "+f"(d[78]), "+f"(d[79])
    : "r"(alo), "r"(blo));
}
__device__ __forceinline__ void wgmma_n128_s64(float (&d)[64], uint32_t alo, uint32_t blo) {
  asm volatile("{\n.reg .b64 da, db;\nmov.b64 da, {%64, 0x40000040};\nmov.b64 db, {%65, 0x80000020};\n"
    "wgmma.mma_async.sync.aligned.m64n128k16.f32.bf16.bf16 "
    "{%0, %1, %2, %3, %4, %5, %6, %7, %8, %9, %10, %11, %12, %13, %14, %15, "
    "%16, %17, %18, %19, %20, %21, %22, %23, %24, %25, %26, %27, %28, %29, %30, %31, "
    "%32, %33, %34, %35, %36, %37, %38, %39, %40, %41, %42, %43, %44, %45, %46, %47, "
    "%48, %49, %50, %51, %52, %53, %54, %55, %56, %57, %58, %59, %60, %61, %62, %63}, "
    "da, db, 1, 1, 1, 1, 0;\n}\n"
    : "+f"(d[0]), "+f"(d[1]), "+f"(d[2]), "+f"(d[3]), "+f"(d[4]), "+f"(d[5]), "+f"(d[6]), "+f"(d[7]),
      "+f"(d[8]), "+f"(d[9]), "+f"(d[10]), "+f"(d[11]), "+f"(d[12]), "+f"(d[13]), "+f"(d[14]), "+f"(d[15]),
      "+f"(d[16]), "+f"(d[17]), "+f"(d[18]), "+f"(d[19]), "+f"(d[20]), "+f"(d[21]), "+f"(d[22]), "+f"(d[23]),
      "+f"(d[24]), "+f"(d[25]), "+f"(d[26]), "+f"(d[27]), "+f"(d[28]), "+f"(d[29]), "+f"(d[30]), "+f"(d[31]),
      "+f"(d[32]), "+f"(d[33]), "+f"(d[34]), "+f"(d[35]), "+f"(d[36]), "+f"(d[37]), "+f"(d[38]), "+f"(d[39]),
      "+f"(d[40]), "+f"(d[41]), "+f"(d[42]), "+f"(d[43]), "+f"(d[44]), "+f"(d[45]), "+f"(d[46]), "+f"(d[47]),
      "+f"(d[48]), "+f"(d[49]), "+f"(d[50]), "+f"(d[51]), "+f"(d[52]), "+f"(d[53]), "+f"(d[54]), "+f"(d[55]),
      "+f"(d[56]), "+f"(d[57]), "+f"(d[58]), "+f"(d[59]), "+f"(d[60]), "+f"(d[61]), "+f"(d[62]), "+f"(d[63])
    : "r"(alo), "r"(blo));
}
__device__ __forceinline__ void wgmma_n128_s32(float (&d)[64], uint32_t alo, uint32_t blo) {
  asm volatile("{\n.reg .b64 da, db;\nmov.b64 da, {%64, 0x40000040};\nmov.b64 db, {%65, 0xc0000010};\n"
    "wgmma.mma_async.sync.aligned.m64n128k16.f32.bf16.bf16 "
    "{%0, %1, %2, %3, %4, %5, %6, %7, %8, %9, %10, %11, %12, %13, %14, %15, "
    "%16, %17, %18, %19, %20, %21, %22, %23, %24, %25, %26, %27, %28, %29, %30, %31, "
    "%32, %33, %34, %35, %36, %37, %38, %39, %40, %41, %42, %43, %44, %45, %46, %47, "
    "%48, %49, %50, %51, %52, %53, %54, %55, %56, %57, %58, %59, %60, %61, %62, %63}, "
    "da, db, 1, 1, 1, 1, 0;\n}\n"
    : "+f"(d[0]), "+f"(d[1]), "+f"(d[2]), "+f"(d[3]), "+f"(d[4]), "+f"(d[5]), "+f"(d[6]), "+f"(d[7]),
      "+f"(d[8]), "+f"(d[9]), "+f"(d[10]), "+f"(d[11]), "+f"(d[12]), "+f"(d[13]), "+f"(d[14]), "+f"(d[15]),
      "+f"(d[16]), "+f"(d[17]), "+f"(d[18]), "+f"(d[19]), "+f"(d[20]), "+f"(d[21]), "+f"(d[22]), "+f"(d[23]),
      "+f"(d[24]), "+f"(d[25]), "+f"(d[26]), "+f"(d[27]), "+f"(d[28]), "+f"(d[29]), "+f"(d[30]), "+f"(d[31]),
      "+f"(d[32]), "+f"(d[33]), "+f"(d[34]), "+f"(d[35]), "+f"(d[36]), "+f"(d[37]), "+f"(d[38]), "+f"(d[39]),
      "+f"(d[40]), "+f"(d[41]), "+f"(d[42]), "+f"(d[43]), "+f"(d[44]), "+f"(d[45]), "+f"(d[46]), "+f"(d[47]),
      "+f"(d[48]), "+f"(d[49]), "+f"(d[50]), "+f"(d[51]), "+f"(d[52]), "+f"(d[53]), "+f"(d[54]), "+f"(d[55]),
      "+f"(d[56]), "+f"(d[57]), "+f"(d[58]), "+f"(d[59]), "+f"(d[60]), "+f"(d[61]), "+f"(d[62]), "+f"(d[63])
    : "r"(alo), "r"(blo));
}

__device__ __forceinline__ void cexp_k(float zr, float zi, float k, float& re, float& im) {
  float mag = ex2(zr * k * 1.4426950408889634f);
  float th = zi * k;
  float q = rintf(th * 0.15915494309189535f);
  float r = fmaf(q, -6.2831854820251465f, th);
  r = fmaf(q, 1.7484555314695172e-7f, r);
  re = mag * __cosf(r);
  im = mag * __sinf(r);
}
__device__ __forceinline__ float2 cmul(float2 a, float2 b) { return make_float2(fmaf(a.x, b.x, -a.y * b.y), fmaf(a.x, b.y, a.y * b.x)); }
__device__ __forceinline__ int slot_round(int y) {
  const int b = (int)__bfloat16_as_ushort(__float2bfloat16_rn((float)y)) - 17024;
  return y < 128 ? y : b;
}

__device__ __forceinline__ void p0_kgen(const Params& p, unsigned char* sm, uint32_t sb, int tid, int b) {
  const int wg = tid >> 7, n = tid & 127, lane = tid & 31, warp = tid >> 5;
  float* scr = reinterpret_cast<float*>(sm + SM_SCR);
  const int d0 = 4 * b + wg * 2;
  const float la0 = ldbf(p.logA + d0 * NMODE + n), la1 = ldbf(p.logA + (d0 + 1) * NMODE + n);
  const float ai0 = ldbf(p.Aim + d0 * NMODE + n), ai1 = ldbf(p.Aim + (d0 + 1) * NMODE + n);
  const float cr0 = ldbf(p.Cre + d0 * NMODE + n), cr1 = ldbf(p.Cre + (d0 + 1) * NMODE + n);
  const float ci0 = ldbf(p.Cim + d0 * NMODE + n), ci1 = ldbf(p.Cim + (d0 + 1) * NMODE + n);
  const float ld0 = ldbf(p.logdt + d0), ld1 = ldbf(p.logdt + d0 + 1);
#pragma unroll
  for (int i = 0; i < 5; i++)
    if (tid + 256 * i < SM_SC / 16) sts128(sb + (tid + 256 * i) * 16, make_uint4(0, 0, 0, 0));
  {
    float m0 = fmaxf(fabsf(cr0), fabsf(ci0)), m1 = fmaxf(fabsf(cr1), fabsf(ci1));
#pragma unroll
    for (int o = 16; o; o >>= 1) { m0 = fmaxf(m0, __shfl_xor_sync(~0u, m0, o)); m1 = fmaxf(m1, __shfl_xor_sync(~0u, m1, o)); }
    if (lane == 0) { scr[warp] = m0; scr[8 + warp] = m1; }
  }
  wg_sync(wg);
  TL(34);
#pragma unroll 1
  for (int cc = 0; cc < 2; cc++) {
    const int c = wg * 2 + cc;
    float cm = fmaxf(fmaxf(scr[cc * 8 + wg * 4], scr[cc * 8 + wg * 4 + 1]), fmaxf(scr[cc * 8 + wg * 4 + 2], scr[cc * 8 + wg * 4 + 3]));
    if (!(cm > 0.0f)) cm = 1.0f;
    const float dt = bf_round(ex2((cc ? ld1 : ld0) * 1.4426950408889634f));
    const float zr = -bf_round(ex2((cc ? la1 : la0) * 1.4426950408889634f)) * dt, zi = (cc ? ai1 : ai0) * dt;
    if (n == 0) reinterpret_cast<float*>(sm + SM_SC)[c] = 2.0f * dt * cm;
    const float icm = 1.0f / cm;
    float2 w1, w8, v1;
    cexp_k(zr, zi, 1.0f, w1.x, w1.y);
    cexp_k(zr, zi, 8.0f, w8.x, w8.y);
    cexp_k(zr, zi, 128.0f, v1.x, v1.y);
    const uint32_t fb = sb + SM_FB + c * (16 * 528) + n * 4;
    {
      float2 l[4];
      l[0] = make_float2(1.0f, 0.0f); l[1] = w8; l[2] = cmul(w8, w8); l[3] = cmul(l[2], w8);
      const float2 w32 = cmul(l[2], l[2]);
#pragma unroll
      for (int j = 0; j < 16; j++) {
        sts32(fb + j * 528, pack_h(l[j & 3].x, l[j & 3].y));
        if (j < 12) l[j & 3] = cmul(l[j & 3], w32);
      }
    }
    w1.y = -w1.y; v1.y = -v1.y;
    float2 bq[8];
    bq[1] = w1; bq[2] = cmul(w1, w1); bq[3] = cmul(bq[2], w1); bq[4] = cmul(bq[2], bq[2]);
    bq[5] = cmul(bq[4], w1); bq[6] = cmul(bq[4], bq[2]); bq[7] = cmul(bq[4], bq[3]);
    const uint32_t fa = sb + SM_FA + c * (48 * 528) + n * 4;
    float2 h[4];
    {
      const float2 v2 = cmul(v1, v1);
      h[0] = make_float2((cc ? cr1 : cr0) * icm, -(cc ? ci1 : ci0) * icm);
      h[1] = cmul(h[0], v1); h[2] = cmul(h[0], v2); h[3] = cmul(h[1], v2);
      v1 = cmul(v2, v2);
    }
    int row = 0;
#pragma unroll
    for (int i = 0; i <= 16; i++) {
      const int step = i < 2 ? 1 : i < 4 ? 2 : i < 8 ? 4 : 8;
#pragma unroll
      for (int q = 0; q < 8; q += step) {
        const float2 tv = q ? cmul(h[i & 3], bq[q]) : h[i & 3];
        sts32(fa + row * 528, pack_h(tv.x, tv.y));
        row++;
      }
      if (i <= 12) h[i & 3] = cmul(h[i & 3], v1);
    }
  }
  wg_sync(wg);
  TL(35);
  {
    const int c = warp >> 1, nt = warp & 1, g = lane >> 2, t = lane & 3;
    float ac[2][3][4];
#pragma unroll
    for (int h = 0; h < 2; h++)
#pragma unroll
      for (int mt = 0; mt < 3; mt++) { ac[h][mt][0] = ac[h][mt][1] = ac[h][mt][2] = ac[h][mt][3] = 0.0f; }
    const uint32_t aaddr = sb + SM_FA + c * (48 * 528) + (lane & 15) * 528 + (lane >> 4) * 16 + nt * 256;
    const uint32_t baddr = sb + SM_FB + c * (16 * 528) + ((lane >> 4) * 8 + (lane & 7)) * 528 + ((lane >> 3) & 1) * 16 + nt * 256;
#pragma unroll 2
    for (int ks = 0; ks < 8; ks++) {
      uint32_t b0, b1, b2, b3;
      ldsm_x4(b0, b1, b2, b3, baddr + ks * 32);
#pragma unroll
      for (int mt = 0; mt < 3; mt++) {
        uint32_t a0, a1, a2, a3;
        ldsm_x4(a0, a1, a2, a3, aaddr + mt * 16 * 528 + ks * 32);
        mma_f16(ac[0][mt], a0, a1, a2, a3, b0, b1);
        mma_f16(ac[1][mt], a0, a1, a2, a3, b2, b3);
      }
    }
    asm volatile("bar.sync %0, 64;" ::"r"(8 + c) : "memory");
    const uint32_t xb = sb + SM_FA + c * (48 * 528) + lane * 16;
#pragma unroll
    for (int mt = 0; mt < 3; mt++) {
      sts128(xb + (nt * 3 + mt) * 512, make_uint4(__float_as_uint(nt ? ac[0][mt][0] : ac[1][mt][0]), __float_as_uint(nt ? ac[0][mt][1] : ac[1][mt][1]),
                                                  __float_as_uint(nt ? ac[0][mt][2] : ac[1][mt][2]), __float_as_uint(nt ? ac[0][mt][3] : ac[1][mt][3])));
    }
    asm volatile("bar.sync %0, 64;" ::"r"(8 + c) : "memory");
    float acc[3][4];
#pragma unroll
    for (int mt = 0; mt < 3; mt++) {
      const uint4 o = lds128(xb + ((nt ^ 1) * 3 + mt) * 512);
      acc[mt][0] = (nt ? ac[1][mt][0] : ac[0][mt][0]) + __uint_as_float(o.x); acc[mt][1] = (nt ? ac[1][mt][1] : ac[0][mt][1]) + __uint_as_float(o.y);
      acc[mt][2] = (nt ? ac[1][mt][2] : ac[0][mt][2]) + __uint_as_float(o.z); acc[mt][3] = (nt ? ac[1][mt][3] : ac[0][mt][3]) + __uint_as_float(o.w);
    }
    __half* kv = reinterpret_cast<__half*>(sm + SM_KV) + c * 648;
    const int j8 = 8 * (nt * 8 + 2 * t);
    const int h00 = g, h01 = 128 + g, h10 = 256 + 128 * (g >> 2) + 2 * (g & 3), h11 = 512 + 128 * (g >> 1) + 4 * (g & 1), h20 = 1024 + 128 * g;
#pragma unroll
    for (int e = 0; e < 2; e++) {
      const int jj = j8 + 8 * e;
      kv[h00 + jj] = __float2half_rn(acc[0][e]);
      kv[h01 + jj] = __float2half_rn(acc[0][2 + e]);
      kv[128 + ((h10 + jj) >> 1)] = __float2half_rn(acc[1][e]);
      kv[256 + ((h11 + jj) >> 2)] = __float2half_rn(acc[1][2 + e]);
      kv[384 + ((h20 + jj) >> 3)] = __float2half_rn(acc[2][e]);
    }
    if (g == 0 && j8 == 0) kv[640] = __float2half_rn(acc[2][2]);
  }
  __syncwarp();
  if (lane == 0) mbar_arrive(sb + SM_BAR + B_KG * 8);
  TL(36);
}

__device__ __forceinline__ void build_tables(uint32_t sb, int tid) {
  const int wg = tid >> 7, n = tid & 127;
  int pb, ps, vlo, vhi;
  uint32_t dst;
  if (n < 67) {
    const bool mid = n >= 65;
    pb = mid ? 1016 + 8 * (n - 65) : 8 * n; ps = 1;
    vlo = mid ? 1022 : 0; vhi = mid ? 1028 : 514;
    dst = SM_TN + (mid ? 584 + 8 * (n - 65) : 16 + 8 * n) * 4;
  } else {
    const int f = n - 67;
    const bool s3 = f >= 20;
    const int st = s3 ? 4 + ((f - 20) >> 3) : (f * 52) >> 8, ch = s3 ? (f - 20) & 7 : f - 5 * st;
    const int o = (st == 0 || st == 4) ? 16 : s3 ? 8 : 4 * st;
    const int x0 = (s3 ? 64 : 32) + 8 * ch;
    pb = 16 * x0 + o; ps = 16;
    vlo = 16 * (s3 ? 64 : 32) + o; vhi = 16 * (s3 ? 127 : (st == 0 ? 62 : 63)) + o;
    dst = SM_TF + ((s3 ? 256 + (st - 4) * 80 - 48 : st * 64 - 16) + x0) * 4;
  }
  if (n < 103) {
#pragma unroll 1
    for (int cc = 0; cc < 2; cc++) {
      const int c = wg * 2 + cc;
      const uint32_t kv = sb + SM_KV + c * 1296;
      uint32_t k[9];
#pragma unroll
      for (int i = 0; i < 9; i++) {
        const int pos = pb + ps * (i - 1);
        uint32_t v = 0;
        if ((unsigned)(pos - vlo) <= (unsigned)(vhi - vlo))
          asm volatile("ld.shared.u16 %0, [%1];" : "=r"(v) : "r"(kv + 2 * slot_round(pos)));
        k[i] = v;
      }
      const uint32_t d = sb + dst + c * (n < 67 ? TN_CH : TF_CH);
      sts128(d, make_uint4(k[1] | (k[0] << 16), k[2] | (k[1] << 16), k[3] | (k[2] << 16), k[4] | (k[3] << 16)));
      sts128(d + 16, make_uint4(k[5] | (k[4] << 16), k[6] | (k[5] << 16), k[7] | (k[6] << 16), k[8] | (k[7] << 16)));
    }
  }
}

constexpr int SM_RAWX = 22528;
constexpr int SM_IMGX = 176128;
constexpr int SM_RAW1 = 192512;
constexpr int SM_IMG2 = 217088;
constexpr int SM_IMG1 = 131072;
__device__ __forceinline__ void tma_2d(uint32_t dst, const CUtensorMap* tm, int c0, int c1, uint32_t bar) {
  asm volatile("cp.async.bulk.tensor.2d.shared::cluster.global.mbarrier::complete_tx::bytes [%0], [%1, {%2, %3}], [%4];"
               ::"r"(dst), "l"(tm), "r"(c0), "r"(c1), "r"(bar) : "memory");
}

__device__ __forceinline__ void p0_producer(const Params& p, unsigned char* sm, uint32_t sb, int ptid, int b, unsigned epoch) {
  const int lane = ptid & 31, pw = ptid >> 5;
  const uint32_t bar = sb + SM_BAR;
  if (ptid == 0) {
    mbar_expect(bar + B_PX * 8, 16384);
    tma_2d(sb + SM_RAWX, &p.tmX, (b & 7) * 64, (b >> 3) * 128, bar + B_PX * 8);
  }
  {
    uint4 xv[4][2];
#pragma unroll
    for (int i = 0; i < 4; i++) {
      const uint4* row = reinterpret_cast<const uint4*>(p.x0 + (size_t)(16 * b + 4 * pw + i) * DM);
      xv[i][0] = __ldg(row + lane); xv[i][1] = __ldg(row + 32 + lane);
    }
    if (ptid == 0) TLP(73);
    float sq[8];
#pragma unroll
    for (int i = 0; i < 4; i++) {
      const uint32_t w[8] = {xv[i][0].x, xv[i][0].y, xv[i][0].z, xv[i][0].w, xv[i][1].x, xv[i][1].y, xv[i][1].z, xv[i][1].w};
      float s = 0.f, q = 0.f;
#pragma unroll
      for (int e = 0; e < 8; e++) { const float a = bf_lo(w[e]), c = bf_hi(w[e]); s += a + c; q = fmaf(a, a, q); q = fmaf(c, c, q); }
      sq[2 * i] = s; sq[2 * i + 1] = q;
    }
    xreduce<8, 16>(sq, lane); xreduce<4, 8>(sq, lane); xreduce<2, 4>(sq, lane);
    sq[0] += __shfl_xor_sync(~0u, sq[0], 2);
    sq[0] += __shfl_xor_sync(~0u, sq[0], 1);
    if ((lane & 3) == 0) reinterpret_cast<float*>(sm + SM_SCR + 64)[8 * pw + (lane >> 2)] = sq[0];
  }
  if (ptid == 0) TLP(74);
  mbar_wait(bar + B_PX * 8, 0);
  if (ptid == 0) TLP(75);
  if (ptid == 32) {
    const int j = b >> 4, pass = (b >> 3) & 1, kb1 = b & 7;
    const int B0 = b < 64 ? 6 * b : 384 + 5 * (b - 64), nb = b < 64 ? 6 : 5;
    mbar_expect(bar + B_PW * 8, 24576 + nb * 2048);
    tma_2d(sb + SM_RAW1, &p.tmG, 176 * j + 96 * pass, kb1 * 64, bar + B_PW * 8);
    tma_2d(sb + SM_RAW1 + 12288, &p.tmU, 176 * j + 96 * pass, kb1 * 64, bar + B_PW * 8);
#pragma unroll 1
    for (int i = 0; i < nb; i++) {
      const int B = B0 + i, img = B >> 3, w = (B >> 2) & 1;
      const int hc = (img * 745) >> 13, kb = img - 11 * hc;
      const int kpos = kb * 64 + (B & 3) * 16;
      const int tau = kpos >> 5;
      const int f = kpos < 640 ? 176 * (4 * (hc >> 2) + (tau & 3)) + 32 * (tau >> 2) + (kpos & 31)
                               : 176 * (4 * (hc >> 2) + ((kpos - 640) >> 4)) + 160;
      tma_2d(sb + SM_IMG2 + i * 2048, &p.tmD, 128 * (hc & 3) + 64 * w, f, bar + B_PW * 8);
    }
  }
  __syncwarp();
  {
    const int mat = lane >> 3, r8 = lane & 7, dl = (pw & 1) * 32 + mat * 8 + r8;
    const uint32_t src = sb + SM_RAWX + ((pw >> 1) * 8 + r8) * 128 + ((((pw & 1) * 4 + mat) ^ r8) << 4);
    const uint32_t dst = sb + SM_IMGX + dl * 128, sw = ((pw >> 1) ^ (dl & 7)) << 4;
#pragma unroll
    for (int i = 0; i < 8; i++) {
      uint32_t r0, r1, r2, r3;
      asm volatile("ldmatrix.sync.aligned.m8n8.x4.trans.shared.b16 {%0,%1,%2,%3}, [%4];" : "=r"(r0), "=r"(r1), "=r"(r2), "=r"(r3)
                   : "r"(src + ((i >> 2) * 64 + (i & 3) * 16) * 128) : "memory");
      stsm_x4(dst + (i >> 2) * 8192 + (sw ^ ((i & 3) << 5)), r0, r1, r2, r3);
    }
  }
  fence_async_smem();
  named_sync_c<4, 128>();
  if (ptid == 0) TLP(76);
  if (ptid == 0) {
    bulk_s2g(reinterpret_cast<unsigned char*>(g_x[0]) + (size_t)b * 16384, sb + SM_IMGX, 16384);
    bulk_s2g(&g_statp[0][16 * b], sb + SM_SCR + 64, 128);
    bulk_commit();
    bulk_wait_all();
    red_release(&g_ctr[C_T1 * 32]);
    TLP(41);
  }
  __syncwarp();
}

__device__ __forceinline__ void p0_pack1(uint32_t sb, int ptid, int b) {
  const int lane = ptid & 31, pw = ptid >> 5;
  const int pass = (b >> 3) & 1;
  mbar_wait(sb + SM_BAR + B_PW * 8, 0);
  if (ptid == 0) TLP(77);
  mbar_wait(sb + SM_BAR + B_KG * 8, 0);
  {
    const int natoms = pass ? 5 : 6;
    const uint32_t img = sb + SM_IMG1;
#pragma unroll 1
    for (int task = pw; task < 12; task += 4) {
      const int khalf = task & 1, up = (task >> 1) & 1, I = task >> 2;
      const int k = khalf * 32 + lane;
      const bool halfgrp = pass && I == 2;
      uint32_t w[16];
#pragma unroll
      for (int q = 0; q < 4; q++) {
        const uint4 t4 = lds128(sb + SM_RAW1 + up * 12288 + k * 192 + I * 64 + q * 16);
        w[4 * q] = t4.x; w[4 * q + 1] = t4.y; w[4 * q + 2] = t4.z; w[4 * q + 3] = t4.w;
      }
      const uint32_t row = img + (k >> 3) * (natoms * 512) + (k & 7) * 64 + (2 * I) * 512;
      const int kx = (k & 7) >> 1;
#pragma unroll
      for (int ip = 0; ip < 4; ip++) {
        const int i = 2 * ip + up;
        const uint4 o = halfgrp ? make_uint4(w[ip & 1], w[2 + (ip & 1)], w[4 + (ip & 1)], w[6 + (ip & 1)]) : make_uint4(w[ip], w[4 + ip], w[8 + ip], w[12 + ip]);
        if (!(halfgrp && ip >= 2)) sts128(row + (i >> 2) * 512 + (((i & 3) ^ kx) << 4), o);
      }
    }
  }
}
__device__ __forceinline__ void p0_pack2(unsigned char* sm, uint32_t sb, int ptid, int b) {
  const int lane = ptid & 31, pw = ptid >> 5;
  const int j = b >> 4, pass = (b >> 3) & 1, kb1 = b & 7;
  {
    const int g = lane >> 2, t = lane & 3, mat = lane >> 3;
#pragma unroll 1
    for (int ti = pw * 6; ti < pw * 6 + 6; ti++) {
      const int up = ti >= 12, ft = up ? ti - 12 : ti;
      float d[4] = {0.f, 0.f, 0.f, 0.f};
#pragma unroll
      for (int kk = 0; kk < 2; kk++) {
        uint32_t b0, b1, b2, b3;
        asm volatile("ldmatrix.sync.aligned.m8n8.x4.trans.shared.b16 {%0,%1,%2,%3}, [%4];" : "=r"(b0), "=r"(b1), "=r"(b2), "=r"(b3)
                     : "r"(sb + SM_RAW1 + up * 12288 + (kk * 32 + mat * 8 + (lane & 7)) * 192 + ft * 16) : "memory");
        asm volatile("mma.sync.aligned.m16n8k16.row.col.f32.bf16.bf16.f32 {%0,%1,%2,%3}, {%4,%4,%4,%4}, {%5,%6}, {%0,%1,%2,%3};"
                     : "+f"(d[0]), "+f"(d[1]), "+f"(d[2]), "+f"(d[3]) : "r"(0x3F803F80u), "r"(b0), "r"(b1));
        asm volatile("mma.sync.aligned.m16n8k16.row.col.f32.bf16.bf16.f32 {%0,%1,%2,%3}, {%4,%4,%4,%4}, {%5,%6}, {%0,%1,%2,%3};"
                     : "+f"(d[0]), "+f"(d[1]), "+f"(d[2]), "+f"(d[3]) : "r"(0x3F803F80u), "r"(b2), "r"(b3));
      }
      const bool hg = pass && ft >= 8;
      const int n = hg ? 16 * (8 + (t & 1)) + 8 * up + 2 * (2 * (ft - 8) + (t >> 1)) : 16 * (4 * (ft >> 2) + t) + 8 * up + 2 * (ft & 3);
      if (g == 0 && !(pass && ft >= 10)) *reinterpret_cast<float2*>(sm + SM_IMG1 + 24576 + n * 4) = make_float2(d[0], d[1]);
    }
  }
  fence_async_smem();
  named_sync_c<4, 128>();
  if (ptid == 0) {
    TLP(42);
    bulk_s2g(g_w1p + (size_t)j * W1_SLICE + (pass ? 196608 + kb1 * 20480 : kb1 * 24576), sb + SM_IMG1, pass ? 20480 : 24576);
    bulk_s2g(&g_csp[kb1][j * 352 + pass * 192], sb + SM_IMG1 + 24576, pass ? 640 : 768);
    bulk_s2g(g_w2p + (size_t)(b < 64 ? 6 * b : 384 + 5 * (b - 64)) * 2048, sb + SM_IMG2, b < 64 ? 12288 : 10240);
    bulk_commit();
    bulk_wait_all();
    red_release(&g_ctr[C_PACK * 32]);
    TLP(43);
  }
  __syncwarp();
}

__device__ __forceinline__ uint32_t lds32(uint32_t a) { uint32_t v; asm volatile("ld.shared.b32 %0, [%1];" : "=r"(v) : "r"(a)); return v; }
__device__ __forceinline__ uint32_t lds32v(uint32_t a) { uint32_t v; asm volatile("ld.volatile.shared.b32 %0, [%1];" : "=r"(v) : "r"(a)); return v; }
__device__ __forceinline__ uint4 lds_toep(uint32_t a) { return make_uint4(lds32v(a), lds32(a + 32), lds32(a - 32), lds32v(a)); }

__device__ __forceinline__ void conv_near(uint32_t sb, int c, int lane, int half, float (&acc)[16][4]) {
  const int g = lane >> 2, t = lane & 3, mat = lane >> 3, n = lane & 7;
  const uint32_t tbase = sb + SM_TN + c * TN_CH + (16 + g - 2 * t) * 4;
  const uint32_t ubase = sb + SM_US + c * US_CH + (mat >> 1) * 256;
  const int cl0 = 2 * n + (mat & 1) + 16;
#pragma unroll 1
  for (int step = 0; step < 2; step++) {
    if (step != half) {
#pragma unroll 1
      for (int m0 = half * 4; m0 < half * 4 + 4; m0++) {
        uint32_t B[16][2];
        const int cl = cl0 - 2 * m0;
        const uint32_t a = ubase + ((cl ^ ((cl >> 3) & 1)) << 4);
#pragma unroll
        for (int q = 0; q < 16; q += 2) ldsm_x4(B[q][0], B[q][1], B[q + 1][0], B[q + 1][1], a + q * 256);
        const uint32_t ta = tbase + m0 * 64;
#pragma unroll
        for (int pp = 0; pp < 4; pp++) {
          const uint4 A = lds_toep(ta + pp * 512);
#pragma unroll
          for (int i1 = pp; i1 < 16; i1++) mma_f16(acc[i1], A.x, A.y, A.z, A.w, B[i1 - pp][0], B[i1 - pp][1]);
        }
        if (m0 == 7) {
          const uint4 A = lds_toep(tbase + (560 + 16 - 16) * 4);
#pragma unroll
          for (int i1 = 7; i1 < 16; i1++) mma_f16(acc[i1], A.x, A.y, A.z, A.w, B[i1 - 7][0], B[i1 - 7][1]);
        }
      }
    } else {
      uint32_t E[12][2];
      const int cl = cl0 - 2 * half;
      const uint32_t a = ubase + ((cl ^ ((cl >> 3) & 1)) << 4);
#pragma unroll
      for (int q = 0; q < 12; q += 2) ldsm_x4(E[q][0], E[q][1], E[q + 1][0], E[q + 1][1], a + q * 256);
      const uint32_t te = tbase + half * 64;
      const uint4 Ae = lds_toep(te + 2048), Af = lds_toep(te + (560 + 32 - 16) * 4);
#pragma unroll
      for (int i1 = 4; i1 < 16; i1++) mma_f16(acc[i1], Ae.x, Ae.y, Ae.z, Ae.w, E[i1 - 4][0], E[i1 - 4][1]);
#pragma unroll
      for (int i1 = 8; i1 < 16; i1++) mma_f16(acc[i1], Af.x, Af.y, Af.z, Af.w, E[i1 - 8][0], E[i1 - 8][1]);
    }
  }
}

__device__ __forceinline__ void conv_prefilter(uint32_t sb, int c, int lane) {
  const uint32_t gb = sb + SM_G + c * G_CH, ubase = sb + SM_YS + c * 4096;
  if (lane < 4) sts128(gb + (lane == 0 ? 0 : lane == 1 ? 3104 : lane == 2 ? 6208 : 8288), make_uint4(0, 0, 0, 0));
#pragma unroll 1
  for (int cc = 1 + lane; cc < 193; cc += 32) {
    float v[22];
#pragma unroll
    for (int h = 0; h < 3; h++) {
      const int uc = cc - 3 + h;
      uint4 q = make_uint4(0, 0, 0, 0);
      if (uc >= 0) q = lds128(ubase + (uc << 4));
      const uint32_t ww[4] = {q.x, q.y, q.z, q.w};
#pragma unroll
      for (int e = 0; e < 4; e++) {
        const int i = 8 * h + 2 * e;
        if (i >= 4 && i < 22) { v[i] = bf_lo(ww[e]); v[i + 1] = bf_hi(ww[e]); }
      }
    }
    float b3[12], o5[8], o7[8], o9[8];
#pragma unroll
    for (int i = 0; i < 12; i++) b3[i] = (v[i + 7] + v[i + 9]) + v[i + 8];
#pragma unroll
    for (int i = 0; i < 8; i++) {
      o5[i] = b3[i] + (v[i + 6] + v[i + 10]);
      o7[i] = o5[i] + (v[i + 5] + v[i + 11]);
      o9[i] = o7[i] + (v[i + 4] + v[i + 12]);
    }
    const uint32_t off = (cc ^ ((cc >> 3) & 1)) << 4;
    sts128(gb + off, make_uint4(pack_h(o5[0], o5[1]), pack_h(o5[2], o5[3]), pack_h(o5[4], o5[5]), pack_h(o5[6], o5[7])));
    sts128(gb + 3104 + off, make_uint4(pack_h(b3[4], b3[5]), pack_h(b3[6], b3[7]), pack_h(b3[8], b3[9]), pack_h(b3[10], b3[11])));
    if (cc < 130) {
      sts128(gb + 6208 + off, make_uint4(pack_h(o9[0], o9[1]), pack_h(o9[2], o9[3]), pack_h(o9[4], o9[5]), pack_h(o9[6], o9[7])));
      sts128(gb + 8288 + off, make_uint4(pack_h(o7[0], o7[1]), pack_h(o7[2], o7[3]), pack_h(o7[4], o7[5]), pack_h(o7[6], o7[7])));
    }
  }
  __syncwarp();
  if (lane == 0) mbar_arrive(sb + SM_BAR + (B_G + c) * 8);
}

__device__ __forceinline__ void conv_far(uint32_t sb, int c, int lane, int half, float (&acc)[16][4]) {
  const uint32_t gb = sb + SM_G + c * G_CH;
  const int g = lane >> 2, t = lane & 3, mat = lane >> 3;
  const uint32_t tb = sb + SM_TF + c * TF_CH + (g - 2 * t) * 4;
  const int rowch = 2 * ((mat >> 1) * 8 + (lane & 7)) + (mat & 1);
#pragma unroll 1
  for (int k = 0; k < 2; k++) {
    const int st = 2 * half + k;
    uint2 B[6];
#pragma unroll
    for (int d = 0; d < 6; d++) { const uint32_t a = tb + (st * 64 + 8 * (d + 4) - 16) * 4; B[d] = make_uint2(lds32(a), lds32(a - 32)); }
    const int ch0 = rowch + (k ^ half);
    const uint32_t ga = gb + k * 3104 + ((ch0 ^ ((ch0 >> 3) & 1)) << 4);
    uint32_t A[6][4];
#pragma unroll
    for (int I = 0; I < 6; I++)
      asm volatile("ldmatrix.sync.aligned.m8n8.x4.trans.shared.b16 {%0,%1,%2,%3}, [%4];" : "=r"(A[I][0]), "=r"(A[I][1]), "=r"(A[I][2]), "=r"(A[I][3]) : "r"(ga + I * 512) : "memory");
#pragma unroll
    for (int I = 0; I < 6; I++)
#pragma unroll
      for (int d = 0; d < 6; d++)
        if (2 * I + d + 4 < 16) mma_f16(acc[2 * I + d + 4], A[I][0], A[I][1], A[I][2], A[I][3], B[d].x, B[d].y);
  }
  {
    uint2 B[8];
#pragma unroll
    for (int d = 0; d < 8; d++) { const uint32_t a = tb + (256 + half * 80 + 8 * (d + 8) - 48) * 4; B[d] = make_uint2(lds32(a), lds32(a - 32)); }
    const int ch0 = rowch + half;
    const uint32_t ga = gb + 6208 + half * 2080 + ((ch0 ^ ((ch0 >> 3) & 1)) << 4);
    uint32_t A[4][4];
#pragma unroll
    for (int I = 0; I < 4; I++)
      asm volatile("ldmatrix.sync.aligned.m8n8.x4.trans.shared.b16 {%0,%1,%2,%3}, [%4];" : "=r"(A[I][0]), "=r"(A[I][1]), "=r"(A[I][2]), "=r"(A[I][3]) : "r"(ga + I * 512) : "memory");
#pragma unroll
    for (int I = 0; I < 4; I++)
#pragma unroll
      for (int d = 0; d < 8; d++)
        if (2 * I + d + 8 < 16) mma_f16(acc[2 * I + d + 8], A[I][0], A[I][1], A[I][2], A[I][3], B[d].x, B[d].y);
  }
}

template <int H>
__device__ __forceinline__ void conv_finish(uint32_t sb, int c, int lane, const float (&acc)[16][4]) {
  const uint32_t b01 = sb + SM_US + c * US_CH + lane * 16, b10 = sb + SM_CX + c * 4096 + lane * 16;
#pragma unroll
  for (int i = 0; i < 8; i++) {
    const int gi = H ? i : 8 + i;
    sts128((H ? b10 : b01) + i * 512, make_uint4(__float_as_uint(acc[gi][0]), __float_as_uint(acc[gi][1]), __float_as_uint(acc[gi][2]), __float_as_uint(acc[gi][3])));
  }
  float sc;
  asm volatile("ld.shared.f32 %0, [%1];" : "=f"(sc) : "r"(sb + SM_SC + c * 4));
  asm volatile("bar.sync %0, 64;" ::"r"(8 + c) : "memory");
  const int mat = lane >> 3, n = lane & 7;
  const int ch0 = 16 * (mat >> 1) + 2 * n + (mat & 1);
  const uint32_t ya = sb + SM_YS + c * 4096 + H * 2048 + ((ch0 ^ ((ch0 >> 3) & 1)) << 4);
#pragma unroll
  for (int i = 0; i < 8; i += 2) {
    uint32_t o[4];
#pragma unroll
    for (int h = 0; h < 2; h++) {
      const uint4 w = lds128((H ? b01 : b10) + (i + h) * 512);
      const int ki = H * 8 + i + h;
      o[2 * h] = pack_bf((acc[ki][0] + __uint_as_float(w.x)) * sc, (acc[ki][1] + __uint_as_float(w.y)) * sc);
      o[2 * h + 1] = pack_bf((acc[ki][2] + __uint_as_float(w.z)) * sc, (acc[ki][3] + __uint_as_float(w.w)) * sc);
    }
    stsm_x4_t(ya + i * 256, o[0], o[1], o[2], o[3]);
  }
}
__device__ __forceinline__ void conv_main(uint32_t sb, int warp, int lane, int gpar, int tl_layer) {
  const int c = warp & 3, half = warp >> 2;
  float acc[16][4];
#pragma unroll
  for (int i = 0; i < 16; i++) { acc[i][0] = acc[i][1] = acc[i][2] = acc[i][3] = 0.0f; }
  conv_near(sb, c, lane, half, acc);
  if (warp == 0) TLP(68 + 3 * tl_layer);
  asm volatile("bar.sync %0, 64;" ::"r"(8 + c) : "memory");
  mbar_wait(sb + SM_BAR + (B_G + c) * 8, gpar);
  if (warp == 0) TLP(67 + 3 * tl_layer);
  conv_far(sb, c, lane, half, acc);
  if (warp == 0) TLP(69 + 3 * tl_layer);
  if (half) conv_finish<1>(sb, c, lane, acc);
  else conv_finish<0>(sb, c, lane, acc);
}

__device__ __forceinline__ void conv_phase(const Params& p, uint32_t sb, int tid, int b, int layer, int gpar, unsigned* done_ctr) {
  const int lane = tid & 31, warp = tid >> 5;
  uint4 x[4], t1[4];
  {
    const __nv_bfloat16* xin = g_x[layer * 2];
#pragma unroll
    for (int c = 0; c < 4; c++) x[c] = __ldcg(reinterpret_cast<const uint4*>(xin + ximg_chunk(tid, 4 * b + c)));
    const uint2 dsk = __ldg(reinterpret_cast<const uint2*>(p.Dskip + 4 * b));
    {
      const float4* sp = reinterpret_cast<const float4*>(&g_statp[layer ? 1 : 0][0]) + tid;
      float4 v[4];
#pragma unroll
      for (int i = 0; i < 4; i++) v[i] = __ldcg(sp + i * 256);
      if (layer) {
        float4 w[12];
#pragma unroll
        for (int c = 0; c < 3; c++)
#pragma unroll
          for (int i = 0; i < 4; i++) w[c * 4 + i] = __ldcg(sp + (c + 1) * (SEQ / 2) + i * 256);
#pragma unroll
        for (int c = 0; c < 3; c++)
#pragma unroll
          for (int i = 0; i < 4; i++) { v[i].x += w[c * 4 + i].x; v[i].y += w[c * 4 + i].y; v[i].z += w[c * 4 + i].z; v[i].w += w[c * 4 + i].w; }
      }
#pragma unroll
      for (int i = 0; i < 4; i++) {
        uint32_t m2, sd2;
        ln_finish2(v[i].x, v[i].y, v[i].z, v[i].w, m2, sd2);
        asm volatile("st.shared.b32 [%0], %1;" ::"r"(sb + SM_CX + (i * 256 + tid) * 4), "r"(m2) : "memory");
        asm volatile("st.shared.b32 [%0], %1;" ::"r"(sb + SM_CX + 4096 + (i * 256 + tid) * 4), "r"(sd2) : "memory");
      }
    }
    named_sync_c<1, 256>();
    uint32_t m2[4];
    float rs[8];
    {
      const uint4 mv = lds128(sb + SM_CX + tid * 16), sv = lds128(sb + SM_CX + 4096 + tid * 16);
      m2[0] = mv.x; m2[1] = mv.y; m2[2] = mv.z; m2[3] = mv.w;
      const uint32_t sw[4] = {sv.x, sv.y, sv.z, sv.w};
#pragma unroll
      for (int e = 0; e < 4; e++) { rs[2 * e] = rcp(bf_lo(sw[e])); rs[2 * e + 1] = rcp(bf_hi(sw[e])); }
    }
    const int ch = tid + 16;
    const uint32_t off = (ch ^ ((ch >> 3) & 1)) << 4;
#pragma unroll
    for (int c = 0; c < 4; c++) {
      const uint32_t dw = c < 2 ? dsk.x : dsk.y;
      const uint32_t d2 = (c & 1) ? __byte_perm(dw, dw, 0x3232) : __byte_perm(dw, dw, 0x1010);
      const uint32_t w[4] = {x[c].x, x[c].y, x[c].z, x[c].w};
      uint32_t o[4], tt[4], ubv[4];
#pragma unroll
      for (int e = 0; e < 4; e++) {
        const uint32_t df = bsub2(w[e], m2[e]);
        const uint32_t ub = pack_bf(bf_lo(df) * rs[2 * e], bf_hi(df) * rs[2 * e + 1]);
        o[e] = pack_h(bf_lo(ub), bf_hi(ub));
        tt[e] = bmul2(ub, d2);
        ubv[e] = ub;
      }
      sts128(sb + SM_YS + c * 4096 + tid * 16, make_uint4(ubv[0], ubv[1], ubv[2], ubv[3]));
      t1[c] = make_uint4(tt[0], tt[1], tt[2], tt[3]);
      sts128(sb + SM_US + c * US_CH + off, make_uint4(o[0], o[1], o[2], o[3]));
    }
    if (tid < 64) sts128(sb + SM_US + (tid >> 4) * US_CH + ((tid & 15) << 4), make_uint4(0, 0, 0, 0));
  }
  named_sync_c<1, 256>();
  if (tid == 0) {
    mbar_arrive(sb + SM_BAR + B_CM * 8);
    if (layer == 0) { bulk_s2g(g_tab + (size_t)b * 17408, sb, TAB_BYTES); bulk_commit(); }
  }
  TL(4 + layer * 17);
  conv_main(sb, warp, lane, gpar, layer);
  TL(5 + layer * 17);
  named_sync_c<1, 256>();
  TL(6 + layer * 17);
  {
    const uint32_t yoff = (tid ^ ((tid >> 3) & 1)) << 4;
    __nv_bfloat16* xout = g_x[layer * 2 + 1];
    uint32_t rb[4];
#pragma unroll
    for (int c = 0; c < 4; c++) {
      const uint4 yv = lds128(sb + SM_YS + c * 4096 + yoff);
      uint4 o;
      o.x = badd2(x[c].x, badd2(yv.x, t1[c].x)); o.y = badd2(x[c].y, badd2(yv.y, t1[c].y));
      o.z = badd2(x[c].z, badd2(yv.z, t1[c].z)); o.w = badd2(x[c].w, badd2(yv.w, t1[c].w));
      __nv_bfloat16* dst = xout + ximg_chunk(tid, 4 * b + c);
      asm volatile("st.global.v4.b32 [%0], {%1, %2, %3, %4};" ::"l"(dst), "r"(o.x), "r"(o.y), "r"(o.z), "r"(o.w) : "memory");
      asm volatile("ld.relaxed.gpu.global.u32 %0, [%1];" : "=r"(rb[c]) : "l"(dst) : "memory");
    }
    if (tid == 0 && layer == 0) bulk_wait_all();
    if (__all_sync(~0u, (rb[0] & rb[1] & rb[2] & rb[3]) != 0xFFFFFFFFu)) named_sync_c<1, 256>();
    if (tid == 0) red_relaxed(done_ctr);
  }
}

struct MlpCtx { int r, ct, rho, wg, warp4, lane, par; };

template <int NACC, int ACC0>
__device__ __forceinline__ void glu_pair(const float (&acc)[NACC], uint32_t cs_addr, const float (&mu)[2], const float (&c1)[2], int t,
                                         uint32_t (&o0)[2], uint32_t (&o1)[2]) {
#pragma unroll
  for (int ip = 0; ip < 2; ip++) {
    float2 cg, cu;
    asm volatile("ld.shared.v4.f32 {%0,%1,%2,%3}, [%4];" : "=f"(cg.x), "=f"(cg.y), "=f"(cu.x), "=f"(cu.y) : "r"(cs_addr + (ip * 16 + 4 * t) * 4));
#pragma unroll
    for (int rr = 0; rr < 2; rr++) {
      float h[2];
#pragma unroll
      for (int e = 0; e < 2; e++) {
        const float tg = fmaf(-mu[rr], e ? cg.y : cg.x, acc[ACC0 + ip * 8 + rr * 2 + e]);
        const float tu = fmaf(-mu[rr], e ? cu.y : cu.x, acc[ACC0 + ip * 8 + 4 + rr * 2 + e]);
        const float a = tu * c1[rr];
        h[e] = fmaf(a, tanh_hw(tg * c1[rr]), a);
      }
      (rr ? o1 : o0)[ip] = pack_bf(h[0], h[1]);
    }
  }
}
__device__ __forceinline__ void glu_store(unsigned char* dst, const uint32_t (&a0)[2], const uint32_t (&a1)[2], const uint32_t (&b0)[2],
                                          const uint32_t (&b1)[2]) {
  asm volatile("st.global.v4.b32 [%0], {%1, %2, %3, %4};" ::"l"(dst), "r"(a0[0]), "r"(a0[1]), "r"(b0[0]), "r"(b0[1]) : "memory");
  asm volatile("st.global.v4.b32 [%0], {%1, %2, %3, %4};" ::"l"(dst + 512), "r"(a1[0]), "r"(a1[1]), "r"(b1[0]), "r"(b1[1]) : "memory");
}
__device__ __forceinline__ void glu_done(uint32_t bar, bool lane0) {
  __syncwarp();
  if (lane0) mbar_arrive(bar);
}

__device__ __forceinline__ void mlp_consumer(const Params& p, unsigned char* sm, uint32_t sb, const MlpCtx cx, int tid, int layer) {
  const uint32_t bar = sb + SM_BAR;
  const int lane = cx.lane, g = lane >> 2, t = lane & 3, wg = cx.wg, par = cx.par;
  const int row0 = wg * 64 + cx.warp4 * 16 + g;
  const bool lane0 = lane == 0;
  const uint32_t sd4 = (sb & 0x3FFFF) >> 4;
  const uint32_t da0 = sd4 + ((SM_X + wg * 8192) >> 4);
  const uint32_t db0 = (sd4 + (SM_W >> 4)) | (32u << 16);

  float accA[96];
  reg_def(accA);
  float accB[80];
  float mu[2], c1[2];
  const int rw = row0;
  unsigned char* const himg = g_h + (size_t)(cx.r * 2 + cx.rho) * (11 * 16384);
  unsigned char* const hdst = himg + cx.ct * 8192 + rw * 64 + ((t ^ ((rw >> 1) & 3)) << 4);
  unsigned char* const hdstH = himg + 163840 + cx.ct * 4096 + rw * 32 + (((t >> 1) ^ ((rw >> 2) & 1)) << 4) + (t & 1) * 8;
#define PASSB_ISSUE(kb)                                                                         \
  {                                                                                             \
    mbar_wait(bar + (B_WFULL + ((kb) & 3)) * 8, ((kb) >> 2) & 1);                               \
    const uint32_t al = da0 + (kb) * 1024, bl = db0 + ((kb) & 3) * 1536;                        \
    wgmma_fence();                                                                              \
    _Pragma("unroll") for (int s = 0; s < 4; s++) wgmma_n160_tt(accB, al + s * 128, bl + s * 320); \
    wgmma_commit();                                                                             \
  }
#define PASSB_RETIRE(kb) { wgmma_wait<1>(); if (lane0) mbar_arrive(bar + (B_WEMPTY + (((kb) - 1) & 3)) * 8); }
  {
    float v[16];
#pragma unroll
    for (int i = 0; i < 16; i++) v[i] = 0.f;
    const int w8 = tid >> 5;
    const uint32_t xs = sb + SM_X + cx.rho * 8192 + lane * 128 + ((w8 ^ (lane & 7)) << 4);
    uint4 w0 = make_uint4(0, 0, 0, 0), w1 = w0;
#define STAT_ACC()                                                                              \
    {                                                                                           \
      const uint32_t wv[8] = {w0.x, w0.y, w0.z, w0.w, w1.x, w1.y, w1.z, w1.w};                  \
      _Pragma("unroll") for (int e = 0; e < 8; e++) {                                           \
        const float a = bf_lo(wv[e]), c = bf_hi(wv[e]);                                         \
        v[4 * (e & 3)] += a; v[4 * (e & 3) + 1] = fmaf(a, a, v[4 * (e & 3) + 1]);               \
        v[4 * (e & 3) + 2] += c; v[4 * (e & 3) + 3] = fmaf(c, c, v[4 * (e & 3) + 3]);           \
      }                                                                                         \
    }
#pragma unroll 1
    for (int kb = 0; kb < 8; kb++) {
      mbar_wait(bar + (B_WFULL + (kb & 3)) * 8, (kb >> 2) & 1);
      if (kb == 0) TL(9 + layer * 17);
      const uint4 n0 = lds128(xs + kb * 16384), n1 = lds128(xs + kb * 16384 + 4096);
      const uint32_t al = da0 + kb * 1024, bl = db0 + (kb & 3) * 1536;
      wgmma_fence();
#pragma unroll
      for (int s = 0; s < 4; s++) wgmma_n192_tt(accA, al + s * 128, bl + s * 384);
      wgmma_commit();
      STAT_ACC();
      w0 = n0; w1 = n1;
      if (kb > 0) { wgmma_wait<1>(); if (lane0) mbar_arrive(bar + (B_WEMPTY + ((kb - 1) & 3)) * 8); }
    }
    STAT_ACC();
    if (layer == 0) TL(38);
    reg_def(accB);
    PASSB_ISSUE(0);
    xreduce<16, 16>(v, lane); xreduce<8, 8>(v, lane); xreduce<4, 4>(v, lane); xreduce<2, 2>(v, lane);
    const float tot = v[0] + __shfl_xor_sync(~0u, v[0], 1);
    const float sq = __shfl_xor_sync(~0u, tot, 2);
    if ((lane & 3) == 0) {
      uint32_t m2, s2;
      ln_finish2(tot, sq, 0.f, 0.f, m2, s2);
      const uint32_t dst = sb + SM_STAT + (cx.rho * 64 + w8 * 8 + (lane >> 2)) * 8;
      asm volatile("st.shared.v2.f32 [%0], {%1, %2};" ::"r"(dst), "f"(bf_lo(m2)), "f"(bf_lo(s2)) : "memory");
      asm volatile("st.async.weak.shared::cluster.mbarrier::complete_tx::bytes.v2.f32 [%0], {%1, %2}, [%3];"
                   ::"r"(mapa(dst, cx.rho ^ 1)), "f"(bf_lo(m2)), "f"(bf_lo(s2)), "r"(mapa(bar + B_STAT * 8, cx.rho ^ 1)) : "memory");
    }
    __syncwarp();
    if (lane == 0) { if (w8 == 0) mbar_expect(bar + B_STAT * 8, 512); else mbar_arrive(bar + B_STAT * 8); }
    if (layer == 0) TL(39);
  }
  wgmma_wait<1>();
  reg_fence(accA);
  TL(10 + layer * 17);
  if (lane0) mbar_arrive(bar + (B_WEMPTY + 3) * 8);

  mbar_wait(bar + B_STAT * 8, par);
  mbar_wait(bar + B_TP * 8, 0);
  TL(17 + layer * 20);
#pragma unroll
  for (int rr = 0; rr < 2; rr++) {
    float2 st;
    asm volatile("ld.shared.v2.f32 {%0,%1}, [%2];" : "=f"(st.x), "=f"(st.y) : "r"(sb + SM_STAT + (row0 + rr * 8) * 8));
    mu[rr] = st.x; c1[rr] = 0.5f * rcp(st.y);
  }
  {
    uint32_t a0[2], a1[2], b0[2], b1[2];
    glu_pair<96, 0>(accA, sb + SM_CS, mu, c1, t, a0, a1);
    PASSB_ISSUE(1);
    glu_pair<96, 16>(accA, sb + SM_CS + 32 * 4, mu, c1, t, b0, b1);
    glu_store(hdst, a0, a1, b0, b1);
    glu_done(bar + B_HA * 8, lane0);
    PASSB_RETIRE(1);
    PASSB_ISSUE(2);
    glu_pair<96, 32>(accA, sb + SM_CS + 64 * 4, mu, c1, t, a0, a1);
    PASSB_RETIRE(2);
    PASSB_ISSUE(3);
    glu_pair<96, 48>(accA, sb + SM_CS + 96 * 4, mu, c1, t, b0, b1);
    glu_store(hdst + 4 * 8192, a0, a1, b0, b1);
    glu_done(bar + B_HB * 8, lane0);
    PASSB_RETIRE(3);
    PASSB_ISSUE(4);
    glu_pair<96, 64>(accA, sb + SM_CS + 128 * 4, mu, c1, t, a0, a1);
    PASSB_RETIRE(4);
    PASSB_ISSUE(5);
    glu_pair<96, 80>(accA, sb + SM_CS + 160 * 4, mu, c1, t, b0, b1);
    glu_store(hdst + 8 * 8192, a0, a1, b0, b1);
    glu_done(bar + B_HC * 8, lane0);
    PASSB_RETIRE(5);
  }
#pragma unroll 1
  for (int kb = 6; kb < 8; kb++) {
    PASSB_ISSUE(kb);
    PASSB_RETIRE(kb);
  }
  wgmma_wait<0>();
  reg_fence(accB);
  TL(11 + layer * 17);
  if (lane0) {
    mbar_arrive(bar + (B_WEMPTY + 3) * 8);
    mbar_arrive_remote(mapa(bar + B_XFREE * 8, cx.rho ^ 1));
  }

  float acc2[64];
  reg_def(acc2);
#define G2_ISSUE(kb)                                                                            \
  {                                                                                             \
    mbar_wait(bar + (B_G2FULL + (kb)) * 8, par);                                                \
    const uint32_t al = sd4 + ((g2_wblk(kb) + wg * 8192) >> 4), bl = (sd4 + (g2_hblk(kb) >> 4)) | (1u << 16); \
    wgmma_fence();                                                                              \
    _Pragma("unroll") for (int s = 0; s < 4; s++) wgmma_n128_s64(acc2, al + s * 128, bl + (s >> 1) * 512 + (s & 1) * 2); \
    wgmma_commit();                                                                             \
  }
#define G2_RETIRE(kb) { wgmma_wait<1>(); if (lane0) mbar_arrive(bar + (B_G2EMPTY + (kb) - 1) * 8); }
  G2_ISSUE(0);
  TL(12 + layer * 17);
  {
    uint32_t a0[2], a1[2], b0[2], b1[2];
    glu_pair<80, 0>(accB, sb + SM_CS + 192 * 4, mu, c1, t, a0, a1);
    G2_ISSUE(1);
    glu_pair<80, 16>(accB, sb + SM_CS + (192 + 32) * 4, mu, c1, t, b0, b1);
    glu_store(hdst + 12 * 8192, a0, a1, b0, b1);
    glu_done(bar + B_HA * 8, lane0);
    G2_RETIRE(1);
    G2_ISSUE(2);
    glu_pair<80, 32>(accB, sb + SM_CS + (192 + 64) * 4, mu, c1, t, a0, a1);
    G2_RETIRE(2);
    G2_ISSUE(3);
    glu_pair<80, 48>(accB, sb + SM_CS + (192 + 96) * 4, mu, c1, t, b0, b1);
    glu_store(hdst + 16 * 8192, a0, a1, b0, b1);
    glu_done(bar + B_HB * 8, lane0);
    G2_RETIRE(3);
    G2_ISSUE(4);
    glu_pair<80, 64>(accB, sb + SM_CS + (192 + 128) * 4, mu, c1, t, a0, a1);
    asm volatile("st.global.v2.b32 [%0], {%1, %2};" ::"l"(hdstH), "r"(a0[0]), "r"(a0[1]) : "memory");
    asm volatile("st.global.v2.b32 [%0], {%1, %2};" ::"l"(hdstH + 256), "r"(a1[0]), "r"(a1[1]) : "memory");
    glu_done(bar + B_HC * 8, lane0);
    G2_RETIRE(4);
  }
#pragma unroll 1
  for (int kb = 5; kb < 10; kb++) {
    G2_ISSUE(kb);
    if (kb == 6) TL(13 + layer * 17);
    G2_RETIRE(kb);
  }
  {
    mbar_wait(bar + (B_G2FULL + 10) * 8, par);
    const uint32_t al = sd4 + ((g2_wblk(10) + wg * 8192) >> 4), bl = (sd4 + (g2_hblk(10) >> 4)) | (1u << 16);
    wgmma_fence();
#pragma unroll
    for (int s = 0; s < 4; s++) wgmma_n128_s32(acc2, al + s * 128, bl + s * 256);
    wgmma_commit();
    G2_RETIRE(10);
  }
  wgmma_wait<0>();
  reg_fence(acc2);
  TL(14 + layer * 17);
  if (lane == 0) mbar_arrive(bar + (B_G2EMPTY + 10) * 8);

  float keep[32];
  {
    mbar_wait(bar + B_XFREE * 8, par);
    const uint32_t rbuf = mapa(sb + SM_XCH + tid * 16, cx.rho ^ 1), rbar = mapa(bar + B_XCH * 8, cx.rho ^ 1);
#pragma unroll
    for (int q = 0; q < 4; q++) {
      uint32_t w[4];
#pragma unroll
      for (int e = 0; e < 4; e++) {
        const int i = 8 * q + 2 * e;
        w[e] = pack_bf(cx.rho ? acc2[i] : acc2[32 + i], cx.rho ? acc2[i + 1] : acc2[33 + i]);
      }
      asm volatile("st.async.weak.shared::cluster.mbarrier::complete_tx::bytes.v4.b32 [%0], {%1,%2,%3,%4}, [%5];"
                   ::"r"(rbuf + q * 4096), "r"(w[0]), "r"(w[1]), "r"(w[2]), "r"(w[3]), "r"(rbar) : "memory");
    }
#pragma unroll
    for (int i = 0; i < 32; i++) keep[i] = cx.rho ? acc2[32 + i] : acc2[i];
    mbar_wait(bar + B_RES * 8, par);
    mbar_wait(bar + B_XCH * 8, par);
    TL(15 + layer * 17);
#pragma unroll
    for (int q = 0; q < 4; q++) {
      const uint4 v = lds128(sb + SM_XCH + q * 4096 + tid * 16);
      const uint32_t w[4] = {v.x, v.y, v.z, v.w};
#pragma unroll
      for (int e = 0; e < 4; e++) { keep[8 * q + 2 * e] += bf_lo(w[e]); keep[8 * q + 2 * e + 1] += bf_hi(w[e]); }
    }
  }
  const int mat = lane >> 3;
  const int rrow = cx.warp4 * 16 + (mat & 1) * 8 + (lane & 7);
  uint32_t xo[16];
#pragma unroll
  for (int i = 0; i < 8; i += 2) {
    uint32_t r0, r1, r2, r3;
    ldsm_x4(r0, r1, r2, r3, sb + SM_RES + wg * 8192 + rrow * 128 + (((i + (mat >> 1)) ^ (rrow & 7)) << 4));
    const uint32_t rv[4] = {r0, r1, r2, r3};
#pragma unroll
    for (int q = 0; q < 4; q++) {
      xo[2 * i + q] = badd2(rv[q], pack_bf(keep[4 * i + 2 * q], keep[4 * i + 2 * q + 1]));
    }
  }
  if (layer == 0) {
#pragma unroll
    for (int i = 0; i < 8; i += 2)
      stsm_x4(sb + SM_RES + wg * 8192 + rrow * 128 + (((i + (mat >> 1)) ^ (rrow & 7)) << 4), xo[2 * i], xo[2 * i + 1], xo[2 * i + 2], xo[2 * i + 3]);
    fence_async_smem();
    named_sync_c<1, 256>();
    if (tid == 0) {
      __nv_bfloat16* dst = g_x[2];
#pragma unroll
      for (int w = 0; w < 2; w++) bulk_s2g(dst + (size_t)(((cx.r * 8 + 2 * cx.ct + w) * 2 + cx.rho) * 4096), sb + SM_RES + w * 8192, 8192);
      bulk_commit();
    }
    {
      const int warp = tid >> 5;
      const uint32_t base = sb + SM_RES + warp * 2048 + (lane & 3) * 4;
      float s0 = 0.f, q0 = 0.f, s1 = 0.f, q1 = 0.f;
#pragma unroll 1
      for (int h = 0; h < 2; h++) {
#pragma unroll
        for (int i = 0; i < 8; i++) {
          uint32_t w;
          asm volatile("ld.shared.b32 %0, [%1];" : "=r"(w) : "r"(base + (h * 8 + i) * 128 + (((lane >> 2) ^ i) << 4)));
          const float a = bf_lo(w), c = bf_hi(w);
          s0 += a; q0 = fmaf(a, a, q0); s1 += c; q1 = fmaf(c, c, q1);
        }
      }
      *reinterpret_cast<float4*>(sm + SM_RED + (warp * 64 + 2 * lane) * 8) = make_float4(s0, q0, s1, q1);
    }
    named_sync_c<1, 256>();
    if (tid < 64) {
      const float* red = reinterpret_cast<const float*>(sm + SM_RED);
      float s = 0.f, q = 0.f;
#pragma unroll
      for (int w = 0; w < 8; w++) { const float2 a = *reinterpret_cast<const float2*>(red + (w * 64 + tid) * 2); s += a.x; q += a.y; }
      *reinterpret_cast<float2*>(sm + SM_RED + 4096 + tid * 8) = make_float2(s, q);
      fence_async_smem();
      named_sync_c<6, 64>();
      if (tid == 0) {
        bulk_s2g(&g_statp[1 + cx.ct][cx.r * 128 + cx.rho * 64], sb + SM_RED + 4096, 512);
        bulk_commit();
        bulk_wait_all();
        red_release(&g_ctr[C_T3 * 32]);
      }
    }
  } else {
    named_sync_c<1, 256>();
#pragma unroll
    for (int i = 0; i < 8; i += 2) {
      const int tok = 8 * (i + (mat >> 1)) + (lane & 7);
      const int ch = wg * 8 + cx.warp4 * 2 + (mat & 1);
      stsm_x4_t(sb + SM_RES + tok * 256 + ((ch ^ (tok & 7)) << 4), xo[2 * i], xo[2 * i + 1], xo[2 * i + 2], xo[2 * i + 3]);
    }
    named_sync_c<1, 256>();
#pragma unroll
    for (int q = 0; q < 4; q++) {
      const int id = q * 256 + tid, tok = id >> 4, ch = id & 15;
      const uint4 v = lds128(sb + SM_RES + tok * 256 + ((ch ^ (tok & 7)) << 4));
      *reinterpret_cast<uint4*>(p.out + (size_t)(cx.r * 128 + cx.rho * 64 + tok) * DM + cx.ct * 128 + ch * 8) = v;
    }
  }
}

__device__ __forceinline__ void mlp_helper(unsigned char* sm, uint32_t sb, const MlpCtx cx, int hw, int lane, int layer, unsigned epoch, bool first) {
  const uint32_t bar = sb + SM_BAR;
  if (first && hw == 0) {
    if (lane == 0) poll_ge(&g_ctr[C_PACK * 32], (epoch + 1) * NCTA);
    __syncwarp();
    const float4* src = reinterpret_cast<const float4*>(&g_csp[0][(cx.rho * 4 + cx.ct) * 352]);
#pragma unroll 1
    for (int i = lane; i < 88; i += 32) {
      float4 s = make_float4(0.f, 0.f, 0.f, 0.f);
#pragma unroll
      for (int q = 0; q < 8; q++) { const float4 a = __ldcg(src + q * (8 * 88) + i); s.x += a.x; s.y += a.y; s.z += a.z; s.w += a.w; }
      float* dst = reinterpret_cast<float*>(sm + SM_CS) + (i >> 2) * 16 + (i & 1) * 8 + ((i >> 1) & 1) * 2;
      *reinterpret_cast<float2*>(dst) = make_float2(s.x, s.y);
      *reinterpret_cast<float2*>(dst + 4) = make_float2(s.z, s.w);
    }
    __syncwarp();
    if (lane == 0) mbar_arrive(bar + B_TP * 8);
  }
  const unsigned char* himg = g_h + (size_t)(cx.r * 2 + cx.rho) * (11 * 16384);
#pragma unroll 1
  for (int ph = 0; ph < 2; ph++) {
    const int gq = hw + 3 * ph;
    mbar_wait(bar + (hw == 0 ? B_HA : hw == 1 ? B_HB : B_HC) * 8, ph);
    readback_lines(himg + (gq < 5 ? (4 * gq + cx.ct) * 8192 : 163840 + cx.ct * 4096) + lane * 128, gq == 5 ? 0 : 4096);
    if (lane == 0) {
      red_relaxed(&g_ctr2[((layer * 6 + gq) * 32 + cx.r * 2 + cx.rho) * 32]);
      if (layer == 1 && (gq == 2 || gq == 3)) TLP(59 + 2 * (gq - 2));
    }
    __syncwarp();
  }
}

__device__ __forceinline__ bool elect_one() {
  uint32_t p;
  asm volatile("{\n.reg .pred P;\nelect.sync _|P, 0xffffffff;\nselp.u32 %0, 1, 0, P;\n}" : "=r"(p));
  return p;
}
__device__ __forceinline__ void load_w(uint32_t sb, int j, int i) {
  const uint32_t bar = sb + SM_BAR + (B_WFULL + (i & 3)) * 8;
  const uint32_t bytes = i < 8 ? 24576 : 20480;
  const unsigned char* src = g_w1p + (size_t)j * W1_SLICE + (i < 8 ? i * 24576 : 196608 + (i - 8) * 20480);
  if (elect_one()) {
    mbar_expect(bar, i < 8 ? 24576 + 16384 : 20480);
    bulk_g2s(sb + SM_W + (i & 3) * 24576, src, bytes, bar);
  }
}
__device__ __forceinline__ void load_tab(uint32_t sb, int b) {
  const uint32_t bar = sb + SM_BAR + B_PT * 8;
  if (elect_one()) {
    mbar_expect(bar, TAB_BYTES);
    bulk_g2s(sb, g_tab + (size_t)b * 17408, TAB_BYTES, bar);
  }
}

__device__ __forceinline__ void load_blk(uint32_t dst, const unsigned char* src, uint32_t bytes, uint32_t fb, uint32_t arm) {
  if (elect_one()) {
    if (arm) mbar_expect(fb, arm);
    bulk_g2s(dst, src, bytes, fb);
  }
}
__device__ __forceinline__ void mlp_producer(uint32_t sb, const MlpCtx cx, int b, int layer, unsigned epoch, bool next_conv) {
  const uint32_t bar = sb + SM_BAR;
  const int j = cx.rho * 4 + cx.ct, par = cx.par;
  const unsigned char* xin = reinterpret_cast<const unsigned char*>(g_x[layer * 2 + 1]) + (size_t)cx.r * 131072;
  const unsigned char* himg = g_h + (size_t)(cx.r * 2 + cx.rho) * (11 * 16384);
  const unsigned char* w2 = g_w2p + (size_t)j * (11 * 16384);
  const unsigned* flag = &g_ctr2[(layer * 6 * 32 + cx.r * 2 + cx.rho) * 32];
  const unsigned ftgt = (epoch + 1) * 4;
#define POLL_H(gq) poll_ge(flag + (gq) * 32 * 32, ftgt)
#define LD_X(kb) load_blk(sb + SM_X + (kb) * 16384, xin + (kb) * 16384, 16384, bar + (B_WFULL + ((kb) & 3)) * 8, 0)
#define LD_W2(kb) load_blk(sb + g2_wblk(kb), w2 + (kb) * 16384, 16384, bar + (B_G2FULL + (kb)) * 8, 32768)
#define LD_H(kb) load_blk(sb + g2_hblk(kb), himg + (kb) * 16384, 16384, bar + (B_G2FULL + (kb)) * 8, 0)
#define WAIT_WE(s, ph) mbar_wait(bar + (B_WEMPTY + (s)) * 8, ph)
  poll_ge(&g_ctr[(layer == 0 ? C_T2 : C_T4) * 32], (epoch + 1) * NCTA);
  TLP(44 + layer * 8);
#pragma unroll 1
  for (int kb = 0; kb < 4; kb++) LD_X(kb);
  if (elect_one()) mbar_expect(bar + B_XCH * 8, 16384);
  TLP(45 + layer * 8);
#pragma unroll 1
  for (int i = 4; i < 12; i++) {
    WAIT_WE(i & 3, ((i >> 2) - 1) & 1);
    load_w(sb, j, i);
    if (i < 8) LD_X(i);
  }
#pragma unroll 1
  for (int kb = 0; kb < 4; kb++) {
    WAIT_WE(kb, 0);
    load_w(sb, j, 12 + kb);
    if (kb < 3) LD_W2(kb);
  }
  TLP(46 + layer * 8);
  POLL_H(0);
  TLP(47 + layer * 8);
  LD_H(0);
  WAIT_WE(0, 1); LD_H(1); LD_W2(3);
  WAIT_WE(1, 1); LD_W2(4); POLL_H(1); LD_H(2); LD_H(3);
  WAIT_WE(2, 1); POLL_H(2); LD_H(4);
  WAIT_WE(3, 1); LD_W2(5); LD_H(5);
#pragma unroll 1
  for (int kb = 6; kb < 9; kb++) { mbar_wait(bar + (B_G2EMPTY + kb - 6) * 8, par); LD_W2(kb); }
  TLP(48 + layer * 8);
  POLL_H(3);
  TLP(49 + layer * 8);
  LD_H(6); LD_H(7);
  mbar_wait(bar + (B_G2EMPTY + 3) * 8, par); LD_W2(9);
  mbar_wait(bar + (B_G2EMPTY + 4) * 8, par); LD_W2(10);
  POLL_H(4);
  LD_H(8); LD_H(9);
  POLL_H(5);
  LD_H(10);
  mbar_wait(bar + (B_G2EMPTY + 5) * 8, par);
  load_blk(sb + SM_RES, xin + (4 * cx.ct + cx.rho) * 8192, 8192, bar + B_RES * 8, 16384);
  load_blk(sb + SM_RES + 8192, xin + (4 * cx.ct + cx.rho + 2) * 8192, 8192, bar + B_RES * 8, 0);
  if (next_conv) {
    mbar_wait(bar + (B_G2EMPTY + 8) * 8, par);
    load_tab(sb, b);
  }
}

__global__ void __cluster_dims__(2, 1, 1) __launch_bounds__(NTHREADS, 1) s4d_glu_megakernel(const __grid_constant__ Params p) {
  extern __shared__ __align__(1024) unsigned char sm[];
  const uint32_t sb = smem_u32(sm);
  int tid;
  asm volatile("mov.u32 %0, %%tid.x;" : "=r"(tid));
  const int b = blockIdx.x;
  const uint32_t bar = sb + SM_BAR;
  if (tid < B_NUM) {
    const int i = tid;
    const bool eight = (i >= B_WEMPTY && i < B_WEMPTY + 4) || (i >= B_G2EMPTY && i < B_G2EMPTY + 11) || i == B_HA || i == B_HB || i == B_HC || i == B_KG || i == B_STAT || i == B_XFREE;
    mbar_init(bar + i * 8, eight ? 8 : 1);
    asm volatile("fence.mbarrier_init.release.cluster;" ::: "memory");
  }
  const unsigned epoch = *reinterpret_cast<volatile unsigned*>(&g_epoch);
  __syncthreads();
  if (!(p.mask & 1)) asm volatile("barrier.cluster.arrive.release.aligned;\nbarrier.cluster.wait.acquire.aligned;" ::: "memory");

  TL(0);
  MlpCtx cx;
  cx.r = b >> 3; cx.ct = (b >> 1) & 3; cx.rho = b & 1;
  cx.wg = __shfl_sync(~0u, (tid >> 7) & 1, 0); cx.warp4 = __shfl_sync(~0u, (tid >> 5) & 3, 0); cx.lane = tid & 31;
  const bool doA1 = p.mask & 1, doB1 = p.mask & 2, doA2 = p.mask & 4, doB2 = p.mask & 8;

  if (__shfl_sync(~0u, tid >> 7, 0) == 2) {
    asm volatile("setmaxnreg.dec.sync.aligned.u32 56;");
    const int ptid = tid - 256;
    const int pwarp = __shfl_sync(~0u, ptid >> 5, 0);
    if (doA1) {
      p0_producer(p, sm, sb, ptid, b, epoch);
      p0_pack1(sb, ptid, b);
      p0_pack2(sm, sb, ptid, b);
    }
    {
      const int j = cx.rho * 4 + cx.ct, plane = ptid & 31;
      int nm = 0, nc = 0;
#pragma unroll 1
      for (int layer = 0; layer < 2; layer++) {
        const bool doA = layer == 0 ? doA1 : doA2, doB = layer == 0 ? doB1 : doB2;
        if (pwarp == 0 && layer == 1 && doA && !doB1) load_tab(sb, b);
        if (doA) {
          mbar_wait(bar + B_CM * 8, nc & 1);
          conv_prefilter(sb, pwarp, plane);
          nc++;
        }
        if (doB) {
          cx.par = nm & 1;
          if (pwarp == 0) {
            if (nm == 0) poll_ge(&g_ctr[C_PACK * 32], (epoch + 1) * NCTA);
            if (doA && layer == 0) mbar_wait(bar + B_KG * 8, 0);
#pragma unroll 1
            for (int i = 0; i < 4; i++) load_w(sb, j, i);
            mlp_producer(sb, cx, b, layer, epoch, layer == 0 && doA2);
          } else {
            mlp_helper(sm, sb, cx, pwarp - 1, plane, layer, epoch, nm == 0);
          }
          nm++;
        }
      }
    }
  } else {
    asm volatile("setmaxnreg.inc.sync.aligned.u32 224;");
    int nm = 0, nc = 0;
#pragma unroll 1
    for (int layer = 0; layer < 2; layer++) {
      if (layer == 0 ? doA1 : doA2) {
        if (layer == 0) {
          TL(1);
          p0_kgen(p, sm, sb, tid, b);
          named_sync_c<1, 256>();
          build_tables(sb, tid);
          fence_async_smem();
        } else {
          mbar_wait(sb + SM_BAR + B_PT * 8, 0);
        }
        TL(2 + layer * 17);
        if (tid == 0) poll_ge(&g_ctr[(layer == 0 ? C_T1 : C_T3) * 32], (epoch + 1) * NCTA);
        named_sync_c<1, 256>();
        TL(3 + layer * 17);
        conv_phase(p, sb, tid, b, layer, nc & 1, &g_ctr[(layer == 0 ? C_T2 : C_T4) * 32]);
        nc++;
        TL(8 + layer * 17);
      }
      if (layer == 0 ? doB1 : doB2) {
        cx.par = nm & 1;
        mlp_consumer(p, sm, sb, cx, tid, layer);
        TL(16 + layer * 17);
        nm++;
      }
    }
    if (doB2 && b == 0 && tid == 0) g_epoch = epoch + 1;
  }
}

}

typedef CUresult (*EncodeTiledFn)(CUtensorMap*, CUtensorMapDataType, cuuint32_t, void*, const cuuint64_t*, const cuuint64_t*, const cuuint32_t*,
                                  const cuuint32_t*, CUtensorMapInterleave, CUtensorMapSwizzle, CUtensorMapL2promotion, CUtensorMapFloatOOBfill);
static void encode_2d(EncodeTiledFn enc, CUtensorMap* tm, const void* base, int rows, int cols, int box_rows, int box_cols, CUtensorMapSwizzle swz) {
  const cuuint64_t gdim[2] = {(cuuint64_t)cols, (cuuint64_t)rows};
  const cuuint64_t gstr[1] = {(cuuint64_t)cols * 2};
  const cuuint32_t box[2] = {(cuuint32_t)box_cols, (cuuint32_t)box_rows};
  const cuuint32_t estr[2] = {1, 1};
  enc(tm, CU_TENSOR_MAP_DATA_TYPE_BFLOAT16, 2, const_cast<void*>(base), gdim, gstr, box, estr, CU_TENSOR_MAP_INTERLEAVE_NONE, swz,
      CU_TENSOR_MAP_L2_PROMOTION_L2_128B, CU_TENSOR_MAP_FLOAT_OOB_FILL_NONE);
}

static void launch_phases(void* const* d_in, void* d_out, int mask, cudaStream_t stream) {
  static EncodeTiledFn enc = nullptr;
  if (!enc) {
    void* fn = nullptr;
    cudaDriverEntryPointQueryResult qr;
    cudaGetDriverEntryPoint("cuTensorMapEncodeTiled", &fn, cudaEnableDefault, &qr);
    enc = (EncodeTiledFn)fn;
  }
  Params p;
  memset(&p, 0, sizeof(p));
  encode_2d(enc, &p.tmX, d_in[0], SEQ, DM, 128, 64, CU_TENSOR_MAP_SWIZZLE_128B);
  encode_2d(enc, &p.tmG, d_in[8], DM, FF, 64, 96, CU_TENSOR_MAP_SWIZZLE_NONE);
  encode_2d(enc, &p.tmU, d_in[9], DM, FF, 64, 96, CU_TENSOR_MAP_SWIZZLE_NONE);
  encode_2d(enc, &p.tmD, d_in[10], FF, DM, 16, 64, CU_TENSOR_MAP_SWIZZLE_128B);
  p.x0 = (const __nv_bfloat16*)d_in[0];
  p.logA = (const __nv_bfloat16*)d_in[1];
  p.Aim = (const __nv_bfloat16*)d_in[2];
  p.Cre = (const __nv_bfloat16*)d_in[3];
  p.Cim = (const __nv_bfloat16*)d_in[4];
  p.logdt = (const __nv_bfloat16*)d_in[5];
  p.Dskip = (const __nv_bfloat16*)d_in[6];
  p.Wg = (const __nv_bfloat16*)d_in[8];
  p.Wu = (const __nv_bfloat16*)d_in[9];
  p.Wd = (const __nv_bfloat16*)d_in[10];
  p.out = (__nv_bfloat16*)d_out;
  p.mask = mask;
  static bool configured = false;
  if (!configured) {
    cudaFuncSetAttribute(s4d_glu_megakernel, cudaFuncAttributeMaxDynamicSharedMemorySize, SM_TOTAL);
    configured = true;
  }
  s4d_glu_megakernel<<<NCTA, NTHREADS, SM_TOTAL, stream>>>(p);
}

extern "C" void kernel_launch(void* const* d_in, const int* in_sizes, int n_in, void* d_out, int out_size) {
  (void)in_sizes; (void)n_in; (void)out_size;
  launch_phases(d_in, d_out, 15, cudaStreamPerThread);
}
```
